```python
import torch

def _softmax(x, axis=-1):
    return torch.softmax(x, dim=axis)

def _gelu(x):
    return torch.nn.functional.gelu(x, approximate='tanh')

def _silu(x):
    return torch.nn.functional.silu(x)

def _sigmoid(x):
    return torch.sigmoid(x)

def _layernorm(x, axis=-1, eps=1e-05):
    m = x.mean(dim=axis, keepdim=True)
    v = x.var(dim=axis, keepdim=True, unbiased=False)
    return (x - m) / torch.sqrt(v + eps)

def _scatter_add(tgt, idx, src, axis=0):
    return tgt.clone().index_add_(axis, idx, src)

def _segment_sum(src, seg, n):
    out = torch.zeros((n,) + src.shape[1:], dtype=src.dtype)
    return out.index_add_(0, seg, src)

def _pad(x, pw):
    flat = tuple((v for pair in reversed(pw) for v in pair))
    return torch.nn.functional.pad(x, flat)
kernel_name = 'adaLN_cond__compressed_kv_cla__dense_activation_relu__decode'

def setup_inputs():

    _w = lambda a: (lambda t: t.to(torch.bfloat16) if t.is_floating_point() else t)(torch.as_tensor(a))

    def _A_setup():
        B, H, Sq, Sk, D, M = (4, 32, 1, 4096, 128, 512)
        Dc = 4 * D
        return {'x': _w((lambda *s: torch.randn(*s, dtype=torch.bfloat16) * 0.05)(B, Sq, M)), 'c_kv': _w((lambda *s: torch.randn(*s, dtype=torch.bfloat16) * 1.6)(B, Sk, Dc)), 'w_q': _w((lambda *s: torch.randn(*s, dtype=torch.bfloat16) * 1.6)(M, H, D) * M ** (-0.5)), 'w_uk': _w((lambda *s: torch.randn(*s, dtype=torch.bfloat16) * 1.6)(Dc, H, D) * Dc ** (-0.5)), 'w_uv': _w((lambda *s: torch.randn(*s, dtype=torch.bfloat16) * 1.6)(Dc, H, D) * Dc ** (-0.5)), 'w_o': _w((lambda *s: torch.randn(*s, dtype=torch.bfloat16) * 1.6)(H, D, M) * (H * D) ** (-0.5))}
    _A_in = _A_setup()

    def _B_setup():
        B, S, D, Dff = (4, 1, 512, 1376)
        return {'x': _w((lambda *s: torch.randn(*s, dtype=torch.bfloat16) * 0.05)(B, S, D)), 'w1': _w((lambda *s: torch.randn(*s, dtype=torch.bfloat16) * 0.05)(D, Dff)), 'w2': _w((lambda *s: torch.randn(*s, dtype=torch.bfloat16) * 0.05)(Dff, D))}
    _B_in = _B_setup()
    return {'A_x': _A_in['x'], 'A_c_kv': _A_in['c_kv'], 'A_w_q': _A_in['w_q'], 'A_w_uk': _A_in['w_uk'], 'A_w_uv': _A_in['w_uv'], 'A_w_o': _A_in['w_o'], 'B_x': _B_in['x'], 'B_w1': _B_in['w1'], 'B_w2': _B_in['w2'], 'c': _w((lambda *s: torch.randn(*s, dtype=torch.bfloat16) * 0.2)(4, 512) * 8.0), 'w_mod': _w((lambda *s: torch.randn(*s, dtype=torch.bfloat16) * 0.2)(512, 6 * 512) * 512 ** (-0.5) * 8.0)}

def reference(A_x, A_c_kv, A_w_q, A_w_uk, A_w_uv, A_w_o, B_x, B_w1, B_w2, c, w_mod):

    def _A_ref(x, c_kv, w_q, w_uk, w_uv, w_o):
        B, Sq, M = (x.shape[0], x.shape[1], x.shape[2])
        Sk = c_kv.shape[1]
        H, D = (w_q.shape[1], w_q.shape[2])
        q = torch.einsum('bqm,mhd->bhqd', x, w_q)
        k = torch.einsum('bkc,chd->bhkd', c_kv, w_uk)
        v = torch.einsum('bkc,chd->bhkd', c_kv, w_uv)
        scores = torch.einsum('bhqd,bhkd->bhqk', q, k) * D ** (-0.5)
        off = Sk - Sq
        qi = torch.arange(Sq)[:, None]
        kj = torch.arange(Sk)[None, :]
        cmask = kj <= qi + off
        scores = torch.where(cmask[None, None], scores, -1000000000.0)
        p = _softmax(scores, axis=-1)
        ctx = torch.einsum('bhqk,bhkd->bhqd', p, v)
        return torch.einsum('bhqd,hdm->bqm', ctx, w_o)

    def _B_ref(x, w1, w2):
        h = torch.einsum('bsd,df->bsf', x, w1)
        zero = torch.zeros_like(h)
        h = torch.maximum(h, zero)
        return torch.einsum('bsf,fd->bsd', h, w2)
    x = A_x
    mod = (_silu(c) @ w_mod).reshape(c.shape[0], 6, 1, -1)
    sa, ca, ga, sb, cb, gb = (mod[:, 0].clone(), mod[:, 1].clone(), mod[:, 2].clone(), mod[:, 3].clone(), mod[:, 4].clone(), mod[:, 5].clone())
    h = _layernorm(x, axis=-1) * (1 + ca) + sa
    x = x + ga * _A_ref(h, A_c_kv, A_w_q, A_w_uk, A_w_uv, A_w_o)
    h = _layernorm(x, axis=-1) * (1 + cb) + sb
    x = x + gb * _B_ref(h, B_w1, B_w2)
    return x
```

```cpp
#include <cuda_runtime.h>
#include <cuda_bf16.h>
#include <cuda.h>
#include <stdint.h>
#include <stdio.h>

namespace {

constexpr int NCTA = 128;
constexpr int NTHREADS = 320;
constexpr int NFFN = 86;
#define WINDOW 8
#define WINDOW_S WINDOW
#define WINDOW_T WINDOW
#define DT_F 350
#define DT_0 0
#define DT_S 330
#define DT_T 350
#define DT_T2 DT_T
#define POLLGAP 200
#define HOPDELAY 400

constexpr uint32_t OFF_KV = 0;
constexpr uint32_t OFF_X = 131072;
constexpr uint32_t OFF_Y = 163840;
constexpr uint32_t OFF_Z = 196608;
constexpr uint32_t OFF_P = 212992;
constexpr uint32_t OFF_S = 221184;
constexpr uint32_t OFF_ACT = 225344;
constexpr uint32_t OFF_RED = 227648;
constexpr uint32_t OFF_BAR = 229696;
constexpr uint32_t OFF_MISC = 230208;
constexpr uint32_t SMEM_BYTES = 230720;
constexpr uint32_t OFF_STG = OFF_KV;
constexpr uint32_t OFF_W2 = OFF_KV + 32768;
constexpr uint32_t OFF_SBCB = OFF_KV + 49152;
constexpr uint32_t OFF_SCR = OFF_KV + 65536;

enum {
    B_WQ = 0,
    B_WUK = 4,
    B_KV = 8,
    B_MOD = 24,
    B_WUV = 26,
    B_WO = 30,
    B_W1 = 34,
    B_W2 = 36,
    B_QABS = 38,
    B_YFREE = 39,
    B_XFREE = 40,
    B_ZFREE = 41,
    B_KV0FREE = 42,
    B_P3 = 43,
    B_CLR2 = 44,
    B_MODV = 45,
    B_WA = 46,
    B_EP = 47,
    B_COUNT = 48
};

struct alignas(64) Params {
    CUtensorMap kv, wq, wuk, wuv, wo, w1, w2, wmod, qabs, wmoda;
    const __nv_bfloat16* x;
    const __nv_bfloat16* c;
    const __nv_bfloat16* wmodp;
    __nv_bfloat16* out;
};

__device__ uint4 g_H[128 * 32];
__device__ uint4 g_Q[128 * 128];
__device__ __nv_bfloat16 g_qabs[4 * 32 * 512];
__device__ uint4 g_part[128 * 4 * 32 * 16];
__device__ uint4 g_stat[8 * 128 * 2];
__device__ uint4 g_C[128 * 128];
__device__ uint4 g_O[128 * 512];
__device__ uint4 g_X1[128 * 8];
__device__ uint4 g_F[NFFN * 512];
__device__ uint4 g_M[4 * 512];
__device__ __align__(128) unsigned int g_sync[5 * 32];

__device__ __forceinline__ uint32_t smem_u32(const void* p) { return (uint32_t)__cvta_generic_to_shared(p); }
__device__ __forceinline__ void mbar_init(uint32_t bar, int cnt) { asm volatile("mbarrier.init.shared::cta.b64 [%0], %1;" ::"r"(bar), "r"(cnt) : "memory"); }
__device__ __forceinline__ void mbar_expect_tx(uint32_t bar, uint32_t bytes) { asm volatile("mbarrier.arrive.expect_tx.shared::cta.b64 _, [%0], %1;" ::"r"(bar), "r"(bytes) : "memory"); }
__device__ __forceinline__ void mbar_arrive(uint32_t bar) { asm volatile("mbarrier.arrive.shared::cta.b64 _, [%0];" ::"r"(bar) : "memory"); }
constexpr int SPIN_LIMIT = 1 << 20;
__device__ __forceinline__ void mbar_wait(uint32_t bar) {
    asm volatile("{\n.reg .pred p;\n.reg .u32 n;\nmov.u32 n, 0;\n"
                 "LW:\nmbarrier.try_wait.parity.shared::cta.b64 p, [%0], 0;\n@p bra LD;\n"
                 "add.u32 n, n, 1;\nsetp.lt.u32 p, n, 4194304;\n@p bra LW;\nLD:\n}" ::"r"(bar) : "memory");
}
__device__ __forceinline__ bool mbar_test(uint32_t bar) {
    uint32_t ok;
    asm volatile("{\n.reg .pred p;\nmbarrier.test_wait.parity.shared::cta.b64 p, [%1], 0;\nselp.u32 %0, 1, 0, p;\n}" : "=r"(ok) : "r"(bar) : "memory");
    return ok;
}
__device__ __forceinline__ void mbar_wait_n(uint32_t bar, int n) {
#pragma unroll 1
    for (int k = 0; k < n; k++) mbar_wait(bar + k * 8);
}
__device__ __forceinline__ void bar_main() { asm volatile("bar.sync 1, 256;" ::: "memory"); }
__device__ __forceinline__ void fence_async_smem() { asm volatile("fence.proxy.async.shared::cta;" ::: "memory"); }

__device__ __forceinline__ uint4 ld128(const uint4* p) {
    uint4 v;
    asm volatile("{\n.reg .b128 t;\n.reg .b64 lo, hi;\nld.relaxed.gpu.global.b128 t, [%4];\nmov.b128 {lo, hi}, t;\nmov.b64 {%0,%1}, lo;\nmov.b64 {%2,%3}, hi;\n}"
                 : "=r"(v.x), "=r"(v.y), "=r"(v.z), "=r"(v.w) : "l"(p) : "memory");
    return v;
}
__device__ __forceinline__ void st128(uint4* p, uint4 v) {
    asm volatile("{\n.reg .b128 t;\n.reg .b64 lo, hi;\nmov.b64 lo, {%1,%2};\nmov.b64 hi, {%3,%4};\nmov.b128 t, {lo, hi};\nst.relaxed.gpu.global.b128 [%0], t;\n}"
                 ::"l"(p), "r"(v.x), "r"(v.y), "r"(v.z), "r"(v.w) : "memory");
}
__device__ __forceinline__ uint4 ldnc128_if(const void* p, bool c) {
    uint4 v;
    asm volatile("{\n.reg .pred p;\nsetp.ne.u32 p, %5, 0;\nmov.u32 %0, 0;\nmov.u32 %1, 0;\nmov.u32 %2, 0;\nmov.u32 %3, 0;\n@p ld.global.nc.v4.u32 {%0,%1,%2,%3}, [%4];\n}"
                 : "=r"(v.x), "=r"(v.y), "=r"(v.z), "=r"(v.w) : "l"(p), "r"((uint32_t)c));
    return v;
}
__device__ __forceinline__ uint32_t ldnc32(const void* p) { uint32_t v; asm volatile("ld.global.nc.u32 %0, [%1];" : "=r"(v) : "l"(p)); return v; }
__device__ __forceinline__ uint32_t ldnc16(const void* p) { uint32_t v; asm volatile("ld.global.nc.u16 %0, [%1];" : "=r"(v) : "l"(p)); return v; }
__device__ __forceinline__ unsigned int ld_epoch(const unsigned int* p) { unsigned int v; asm volatile("ld.relaxed.gpu.global.u32 %0, [%1];" : "=r"(v) : "l"(p)); return v; }
__device__ __forceinline__ void put4(uint4* p, float a, float b, float c, float d, uint32_t tag) {
    st128(p, make_uint4((__float_as_uint(a) & ~3u) | tag, __float_as_uint(b), __float_as_uint(c), __float_as_uint(d)));
}
__device__ __forceinline__ float4 as_f4(uint4 v) {
    return make_float4(__uint_as_float(v.x & ~3u), __uint_as_float(v.y), __uint_as_float(v.z), __uint_as_float(v.w));
}
__device__ __forceinline__ void add4(float4& a, const float4& b) { a.x += b.x; a.y += b.y; a.z += b.z; a.w += b.w; }
__device__ __forceinline__ float4 get4(const uint4* p, bool act, uint32_t tag) {
    uint4 v = make_uint4(tag, 0, 0, 0);
    int it = 0;
#pragma unroll 1
    do { if (act) v = ld128(p); } while (!__all_sync(~0u, (v.x & 3u) == tag) && ++it < SPIN_LIMIT);
    return as_f4(v);
}
__device__ __forceinline__ float4 get4sum2(const uint4* p0, const uint4* p1, bool act1, uint32_t tag) {
    uint4 u, v = make_uint4(tag, 0, 0, 0);
    int it = 0;
#pragma unroll 1
    do { u = ld128(p0); if (act1) v = ld128(p1); } while (!__all_sync(~0u, (u.x & 3u) == tag && (v.x & 3u) == tag) && ++it < SPIN_LIMIT);
    float4 a = as_f4(u);
    add4(a, make_float4(__uint_as_float(v.x & ~3u), __uint_as_float(v.y), __uint_as_float(v.z), __uint_as_float(v.w)));
    return a;
}

__device__ __forceinline__ float4 get4sum4(const uint4* p0, int stride, uint32_t tag) {
    uint4 u0, u1, u2, u3;
    int it = 0;
#pragma unroll 1
    do { u0 = ld128(p0); u1 = ld128(p0 + stride); u2 = ld128(p0 + 2 * stride); u3 = ld128(p0 + 3 * stride); }
    while (!__all_sync(~0u, ((u0.x ^ tag) & 3u) == 0 && ((u1.x ^ tag) & 3u) == 0 && ((u2.x ^ tag) & 3u) == 0 && ((u3.x ^ tag) & 3u) == 0) && ++it < SPIN_LIMIT);
    float4 a = as_f4(u0), b = as_f4(u2);
    add4(a, as_f4(u1));
    add4(b, as_f4(u3));
    add4(a, b);
    return a;
}
__device__ __forceinline__ uint32_t pack_bf16(float lo, float hi) {
    uint32_t r;
    asm("cvt.rn.bf16x2.f32 %0, %1, %2;" : "=r"(r) : "f"(hi), "f"(lo));
    return r;
}
__device__ __forceinline__ float bf_lo(uint32_t u) { return __uint_as_float(u << 16); }
__device__ __forceinline__ float bf_hi(uint32_t u) { return __uint_as_float(u & 0xffff0000u); }
__device__ __forceinline__ float ex2(float x) { float y; asm("ex2.approx.ftz.f32 %0, %1;" : "=f"(y) : "f"(x)); return y; }

__device__ __forceinline__ void ldsm4(uint32_t (&r)[4], uint32_t addr) {
    asm volatile("ldmatrix.sync.aligned.m8n8.x4.shared.b16 {%0,%1,%2,%3}, [%4];" : "=r"(r[0]), "=r"(r[1]), "=r"(r[2]), "=r"(r[3]) : "r"(addr) : "memory");
}
__device__ __forceinline__ void ldsm4t(uint32_t (&r)[4], uint32_t addr) {
    asm volatile("ldmatrix.sync.aligned.m8n8.x4.trans.shared.b16 {%0,%1,%2,%3}, [%4];" : "=r"(r[0]), "=r"(r[1]), "=r"(r[2]), "=r"(r[3]) : "r"(addr) : "memory");
}
__device__ __forceinline__ void stsm4t(uint32_t addr, uint32_t r0, uint32_t r1, uint32_t r2, uint32_t r3) {
    asm volatile("stmatrix.sync.aligned.m8n8.x4.trans.shared.b16 [%0], {%1,%2,%3,%4};" ::"r"(addr), "r"(r0), "r"(r1), "r"(r2), "r"(r3) : "memory");
}
__device__ __forceinline__ void mma16816(float (&d)[4], const uint32_t (&a)[4], uint32_t b0, uint32_t b1) {
    asm volatile("mma.sync.aligned.m16n8k16.row.col.f32.bf16.bf16.f32 {%0,%1,%2,%3}, {%4,%5,%6,%7}, {%8,%9}, {%0,%1,%2,%3};"
                 : "+f"(d[0]), "+f"(d[1]), "+f"(d[2]), "+f"(d[3]) : "r"(a[0]), "r"(a[1]), "r"(a[2]), "r"(a[3]), "r"(b0), "r"(b1));
}
__device__ __forceinline__ void sts32(uint32_t a, uint32_t v) { asm volatile("st.shared.b32 [%0], %1;" ::"r"(a), "r"(v) : "memory"); }
__device__ __forceinline__ void sts16(uint32_t a, float v) {
    __nv_bfloat16 h = __float2bfloat16_rn(v);
    asm volatile("st.shared.b16 [%0], %1;" ::"r"(a), "h"(*reinterpret_cast<unsigned short*>(&h)) : "memory");
}
__device__ __forceinline__ void stsf(uint32_t a, float v) { asm volatile("st.shared.f32 [%0], %1;" ::"r"(a), "f"(v) : "memory"); }
__device__ __forceinline__ void stsf4(uint32_t a, float4 v) { asm volatile("st.shared.v4.f32 [%0], {%1,%2,%3,%4};" ::"r"(a), "f"(v.x), "f"(v.y), "f"(v.z), "f"(v.w) : "memory"); }
__device__ __forceinline__ uint32_t lds32(uint32_t a) { uint32_t v; asm volatile("ld.shared.b32 %0, [%1];" : "=r"(v) : "r"(a) : "memory"); return v; }
__device__ __forceinline__ float ldsf(uint32_t a) { float v; asm volatile("ld.shared.f32 %0, [%1];" : "=f"(v) : "r"(a) : "memory"); return v; }
__device__ __forceinline__ float2 ldsf2(uint32_t a) { float2 v; asm volatile("ld.shared.v2.f32 {%0,%1}, [%2];" : "=f"(v.x), "=f"(v.y) : "r"(a) : "memory"); return v; }
__device__ __forceinline__ float4 ldsf4(uint32_t a) { float4 v; asm volatile("ld.shared.v4.f32 {%0,%1,%2,%3}, [%4];" : "=f"(v.x), "=f"(v.y), "=f"(v.z), "=f"(v.w) : "r"(a) : "memory"); return v; }
__device__ __forceinline__ uint4 lds128(uint32_t a) { uint4 v; asm volatile("ld.shared.v4.b32 {%0,%1,%2,%3}, [%4];" : "=r"(v.x), "=r"(v.y), "=r"(v.z), "=r"(v.w) : "r"(a) : "memory"); return v; }

__device__ __forceinline__ void tma2d(uint32_t dst, const CUtensorMap* m, int c0, int c1, uint32_t bar, uint32_t bytes, uint64_t pol) {
    asm volatile("{\n.reg .pred p;\nelect.sync _|p, 0xffffffff;\n"
                 "@p mbarrier.arrive.expect_tx.shared::cta.b64 _, [%2], %6;\n"
                 "@p cp.async.bulk.tensor.2d.shared::cluster.global.mbarrier::complete_tx::bytes.L2::cache_hint [%0], [%1, {%3, %4}], [%2], %5;\n}"
                 ::"r"(dst), "l"(m), "r"(bar), "r"(c0), "r"(c1), "l"(pol), "r"(bytes) : "memory");
}
__device__ __forceinline__ void tma3d(uint32_t dst, const CUtensorMap* m, int c0, int c1, int c2, uint32_t bar, uint32_t bytes, uint64_t pol) {
    asm volatile("{\n.reg .pred p;\nelect.sync _|p, 0xffffffff;\n"
                 "@p mbarrier.arrive.expect_tx.shared::cta.b64 _, [%2], %7;\n"
                 "@p cp.async.bulk.tensor.3d.shared::cluster.global.mbarrier::complete_tx::bytes.L2::cache_hint [%0], [%1, {%3, %4, %5}], [%2], %6;\n}"
                 ::"r"(dst), "l"(m), "r"(bar), "r"(c0), "r"(c1), "r"(c2), "l"(pol), "r"(bytes) : "memory");
}
__device__ __forceinline__ void tma2d_na(uint32_t dst, const CUtensorMap* m, int c0, int c1, uint32_t bar, uint64_t pol) {
    asm volatile("{\n.reg .pred p;\nelect.sync _|p, 0xffffffff;\n"
                 "@p cp.async.bulk.tensor.2d.shared::cluster.global.mbarrier::complete_tx::bytes.L2::cache_hint [%0], [%1, {%3, %4}], [%2], %5;\n}"
                 ::"r"(dst), "l"(m), "r"(bar), "r"(c0), "r"(c1), "l"(pol) : "memory");
}
__device__ __forceinline__ void tma3d_nohint(uint32_t dst, const CUtensorMap* m, int c0, int c1, int c2, uint32_t bar, uint32_t bytes) {
    asm volatile("{\n.reg .pred p;\nelect.sync _|p, 0xffffffff;\n"
                 "@p mbarrier.arrive.expect_tx.shared::cta.b64 _, [%2], %6;\n"
                 "@p cp.async.bulk.tensor.3d.shared::cluster.global.mbarrier::complete_tx::bytes [%0], [%1, {%3, %4, %5}], [%2];\n}"
                 ::"r"(dst), "l"(m), "r"(bar), "r"(c0), "r"(c1), "r"(c2), "r"(bytes) : "memory");
}
__device__ __forceinline__ void bulk_s2g(void* dst, uint32_t src, uint32_t bytes) {
    asm volatile("cp.async.bulk.global.shared::cta.bulk_group [%0], [%1], %2;" ::"l"(dst), "r"(src), "r"(bytes) : "memory");
}
__device__ __forceinline__ void prefetch_map(const CUtensorMap* m) { asm volatile("prefetch.tensormap [%0];" ::"l"(m) : "memory"); }

constexpr uint32_t DESC_HI = 64u | (1u << 30);
__device__ __forceinline__ constexpr uint32_t desc_lo(uint32_t addr) { return ((addr & 0x3FFFF) >> 4) | (1u << 16); }
__device__ __forceinline__ void wg_fence() { asm volatile("wgmma.fence.sync.aligned;" ::: "memory"); }
__device__ __forceinline__ void wg_commit() { asm volatile("wgmma.commit_group.sync.aligned;" ::: "memory"); }
__device__ __forceinline__ void wg_wait0() { asm volatile("wgmma.wait_group.sync.aligned 0;" ::: "memory"); }
template <int TA>
__device__ __forceinline__ void wgmma_n32(float (&d)[16], uint32_t alo, uint32_t blo, int scale_d) {
    asm volatile("{\n.reg .pred p;\n.reg .b64 da, db;\nsetp.ne.b32 p, %18, 0;\nmov.b64 da, {%16, %20};\nmov.b64 db, {%17, %20};\n"
                 "wgmma.mma_async.sync.aligned.m64n32k16.f32.bf16.bf16 "
                 "{%0,%1,%2,%3,%4,%5,%6,%7,%8,%9,%10,%11,%12,%13,%14,%15}, da, db, p, 1, 1, %19, 0;\n}"
                 : "+f"(d[0]), "+f"(d[1]), "+f"(d[2]), "+f"(d[3]), "+f"(d[4]), "+f"(d[5]), "+f"(d[6]), "+f"(d[7]),
                   "+f"(d[8]), "+f"(d[9]), "+f"(d[10]), "+f"(d[11]), "+f"(d[12]), "+f"(d[13]), "+f"(d[14]), "+f"(d[15])
                 : "r"(alo), "r"(blo), "r"(scale_d), "n"(TA), "n"(DESC_HI));
}
template <int N>
__device__ __forceinline__ void reg_fence(float (&d)[N]) {
#pragma unroll
    for (int i = 0; i < N; i++) asm volatile("" : "+f"(d[i])::"memory");
}

#define TS(slot)
#define TS0(slot)

__device__ __forceinline__ unsigned int gtimer_lo() {
    unsigned long long t;
    asm volatile("mov.u64 %0, %globaltimer;" : "=l"(t));
    return (unsigned int)t;
}
__device__ __forceinline__ void spin(int cycles) {
    const unsigned int t0 = clock();
    while (clock() - t0 < (unsigned int)cycles) {}
}
__device__ __forceinline__ unsigned int ld_cnt(const unsigned int* p) {
    unsigned int v;
    asm volatile("ld.relaxed.gpu.global.u32 %0, [%1];" : "=r"(v) : "l"(p) : "memory");
    return v;
}
__device__ __forceinline__ void wait_cnt(const unsigned int* p, unsigned int target) {
    int it = 0;
#pragma unroll 1
    while ((int)(ld_cnt(p) - target) < 0) { if (++it > SPIN_LIMIT) break; }
}
__device__ __forceinline__ void red_cnt(unsigned int* p) { asm volatile("red.relaxed.gpu.global.add.u32 [%0], 1;" ::"l"(p) : "memory"); }

constexpr uint32_t SB = 1024;

__device__ __noinline__ void gemv_y_put(uint4* dst, uint32_t act, uint32_t tag) {
    const int lane = threadIdx.x & 31, warp = threadIdx.x >> 5;
    const int blk = lane >> 3, r8 = lane & 7;
    const int ch = (warp & 3) * 2 + (blk & 1);
    uint32_t arow = SB + OFF_Y + (warp >> 2) * 16384 + ((blk >> 1) * 8 + r8) * 128 + ((ch ^ r8) << 4);
    uint32_t brow = act + (r8 & 3) * 272 + blk * 16;
    float d[4] = {0.f, 0.f, 0.f, 0.f};
#pragma unroll
    for (int k2 = 0; k2 < 4; k2++) {
        uint32_t b[4], a0[4], a1[4];
        ldsm4(b, brow + k2 * 64);
        ldsm4t(a0, arow + (k2 * 32) * 128);
        ldsm4t(a1, arow + (k2 * 32 + 16) * 128);
        mma16816(d, a0, b[0], b[1]);
        mma16816(d, a1, b[2], b[3]);
    }
    if ((lane & 3) < 2) put4(dst + warp * 16 + (lane >> 2) * 2 + (lane & 3), d[0], d[1], d[2], d[3], tag);
}

__device__ __forceinline__ void gemv_512x16(float (&d)[4], uint32_t tile, uint32_t act, int k0, int nk2, int lane) {
    const int blk = lane >> 3, r8 = lane & 7;
    uint32_t arow = tile + (k0 + (blk >> 1) * 8 + r8) * 32 + (((blk & 1) ^ ((r8 >> 2) & 1)) << 4);
    uint32_t brow = act + (r8 & 3) * 1040 + (k0 + blk * 8) * 2;
#pragma unroll 2
    for (int k2 = 0; k2 < nk2; k2++) {
        uint32_t b[4], a0[4], a1[4];
        ldsm4(b, brow);
        ldsm4t(a0, arow);
        ldsm4t(a1, arow + 512);
        mma16816(d, a0, b[0], b[1]);
        mma16816(d, a1, b[2], b[3]);
        brow += 64;
        arow += 1024;
    }
}

__device__ __noinline__ float4 reduce16(const uint4* base, int n, uint32_t tag) {
    const int t = threadIdx.x, lane = t & 31, warp = t >> 5;
    const uint32_t SCR = SB + OFF_SCR;
    const int pp = t >> 2;
    const uint4* p0 = base + (size_t)pp * 512 + blockIdx.x * 4 + (t & 3);
    spin(HOPDELAY);
    float4 a = get4sum2(p0, p0 + 64 * 512, pp + 64 < n, tag);
#pragma unroll
    for (int of = 4; of <= 16; of <<= 1) {
        a.x += __shfl_xor_sync(~0u, a.x, of); a.y += __shfl_xor_sync(~0u, a.y, of);
        a.z += __shfl_xor_sync(~0u, a.z, of); a.w += __shfl_xor_sync(~0u, a.w, of);
    }
    if (lane < 4) stsf4(SCR + (warp * 4 + lane) * 16, a);
    bar_main();
    float4 r = make_float4(0.f, 0.f, 0.f, 0.f);
    if (t < 4) {
#pragma unroll
        for (int w = 0; w < 8; w++) add4(r, ldsf4(SCR + (w * 4 + t) * 16));
    }
    return r;
}
__device__ __forceinline__ void sts_frag(uint32_t base, uint32_t stride, int m, int b0, float x, float y, float z, float w) {
    const uint32_t a = base + b0 * stride + m * 2;
    sts16(a, x); sts16(a + stride, y); sts16(a + 16, z); sts16(a + stride + 16, w);
}

__global__ void __launch_bounds__(NTHREADS, 1) fused_kernel(const __grid_constant__ Params p) {
    extern __shared__ __align__(1024) uint8_t smem[];
    constexpr uint32_t sb = SB;
    const int t = threadIdx.x, lane = t & 31;
    const int warp = __shfl_sync(0xffffffffu, t >> 5, 0);
    const int i = blockIdx.x;
    const int hh = i >> 2, jj = i & 3;
    const int bb = i >> 5, chunk = i & 31;
    auto BAR = [](int k) { return SB + OFF_BAR + k * 8; };
    constexpr uint32_t MISC = SB + OFF_MISC;

    if (warp == 8) {
        if (lane == 0) {
            TS(0);
            prefetch_map(&p.wmoda);
            prefetch_map(&p.wq);
            if (smem_u32(smem) != SB) __trap();
            mbar_init(BAR(B_WA), 1);
#pragma unroll
            for (int k = 0; k < 4; k++) mbar_init(BAR(k), 1);
            asm volatile("fence.mbarrier_init.release.cluster;" ::: "memory");
            fence_async_smem();
        }
        __syncwarp();
        TS(56);
        asm volatile("bar.arrive 4, 320;" ::: "memory");
        uint64_t pol;
        asm volatile("createpolicy.fractional.L2::evict_first.b64 %0, 1.0;" : "=l"(pol));
        if (lane == 0) mbar_expect_tx(BAR(B_WA), 8192);
        __syncwarp();
        tma2d_na(sb + OFF_Z, &p.wmoda, 16 * hh, jj * 128, BAR(B_WA), pol);
        tma2d_na(sb + OFF_Z + 4096, &p.wmoda, 512 + 16 * hh, jj * 128, BAR(B_WA), pol);
        unsigned int due = gtimer_lo() + DT_0;
        auto pace_dt = [&](int it, unsigned int dt) {
            if (it >= WINDOW) mbar_wait(BAR(0) + (it - WINDOW) * 8);
            int spin_it = 0;
#pragma unroll 1
            while ((int)(gtimer_lo() - due) < 0 && ++spin_it < SPIN_LIMIT) {}
            due += dt;
        };
        auto pace = [&](int it) { pace_dt(it, it < B_KV ? DT_F : (it < B_WO ? DT_T : DT_T2)); };
        auto tile128 = [&](const CUtensorMap* m, int first, uint32_t dst) {
#pragma unroll 1
            for (int k = 0; k < 4; k++) {
                if (first == 0 && k == 3) {
                    TS(34);
                    asm volatile("bar.sync 5, 320;" ::: "memory");
                }
                pace(first + k);
                tma2d(dst + k * 8192, m, hh * 128 + (k >> 1) * 64, jj * 128 + (k & 1) * 64, BAR(0) + (first + k) * 8, 8192, pol);
            }
        };
        tile128(&p.wq, B_WQ, sb + OFF_Y);
        TS(57);
        tile128(&p.wuk, B_WUK, sb + OFF_X);
        TS(61);
#pragma unroll 1
        for (int s = 0; s < 16; s++) {
            pace_dt(B_KV + s, mbar_test(BAR(B_QABS)) ? DT_S : DT_F);
            tma2d(sb + OFF_KV + s * 8192, &p.kv, (s & 7) * 64, bb * 4096 + chunk * 128 + (s >> 3) * 64, BAR(B_KV) + s * 8, 8192, pol);
        }
        TS(43);
        mbar_wait(BAR(B_YFREE));
#pragma unroll 1
        for (int k = 0; k < 2; k++) {
            pace(B_MOD + k);
            tma2d(sb + OFF_Z + k * 8192, &p.wmod, 1024 + 16 * i, k * 256, BAR(B_MOD) + k * 8, 8192, pol);
        }
        tile128(&p.wuv, B_WUV, sb + OFF_Y);
        mbar_wait(BAR(B_XFREE));
#pragma unroll 1
        for (int k = 0; k < 4; k++) {
            pace(B_WO + k);
            tma3d(sb + OFF_X + k * 8192, &p.wo, 0, hh * 128 + jj * 32, k * 2, BAR(B_WO) + k * 8, 8192, pol);
        }
        if (i < NFFN) {
            mbar_wait(BAR(B_ZFREE));
#pragma unroll 1
            for (int k = 0; k < 2; k++) {
                pace(B_W1 + k);
                tma2d(sb + OFF_Z + k * 8192, &p.w1, 16 * i, k * 256, BAR(B_W1) + k * 8, 8192, pol);
            }
            mbar_wait(BAR(B_KV0FREE));
#pragma unroll 1
            for (int k = 0; k < 2; k++) {
                pace(B_W2 + k);
                tma3d(sb + OFF_W2 + k * 8192, &p.w2, 0, 16 * i, k * 4, BAR(B_W2) + k * 8, 8192, pol);
            }
        }
        TS(40);
    } else if (warp == 9) {
        unsigned int ep = 0;
        if (lane == 0) {
            ep = ld_epoch(&g_sync[(i % 5) * 32]);
            mbar_init(BAR(B_YFREE), 8);
            mbar_init(BAR(B_XFREE), 4);
            mbar_init(BAR(B_KV0FREE), 8);
            mbar_init(BAR(B_EP), 1);
            asm volatile("fence.mbarrier_init.release.cluster;" ::: "memory");
        }
        __syncwarp();
        asm volatile("bar.arrive 5, 320;" ::: "memory");
        asm volatile("bar.arrive 4, 320;" ::: "memory");
        if (lane < 9) prefetch_map(&p.kv + lane);
        const uint4 z = make_uint4(0, 0, 0, 0);
        st128(&g_H[i * 32 + lane], z);
#pragma unroll
        for (int k = 0; k < 4; k++) st128(&g_Q[i * 128 + k * 32 + lane], z);
        uint32_t xr = 0;
        if (lane < 16) {
            const int V = i * 4 + (lane >> 2), e = lane & 3;
            const int m = (V >> 4) * 16 + ((V & 15) >> 1) + (e >> 1) * 8, b = (V & 1) * 2 + (e & 1);
            xr = ldnc16(p.x + b * 512 + m);
        }
        TS(35);
        asm volatile("bar.sync 6, 288;" ::: "memory");
        TS(30);
        __syncwarp();
        if (lane == 0) { sts32(MISC + 224, ep); sts32(MISC + 236, 0); mbar_arrive(BAR(B_EP)); }
        TS(31);
        mbar_wait(BAR(B_EP));
        ep = lds32(MISC + 224);
        const uint32_t tag = 1u + 2u * (ep & 1u);
        if (lane < 16) stsf(MISC + 32 + lane * 4, __uint_as_float(xr << 16));
        mbar_wait(BAR(B_P3));
        wait_cnt(&g_sync[4 * 32 + 1], (ep + 1u) * 128u);
        __syncwarp();
        tma3d_nohint(sb + OFF_X, &p.qabs, 0, bb * 32, 0, BAR(B_QABS), 32768);
        TS(41);
#pragma unroll 1
        for (int k = 0; k < 4; k++) st128(&g_C[i * 128 + k * 32 + lane], z);
        if (lane < 8) st128(&g_X1[i * 8 + lane], z);
        if (lane < 16) st128(&g_M[i * 16 + lane], z);
#pragma unroll 1
        for (int k = 0; k < 16; k++) { st128(&g_O[i * 512 + k * 32 + lane], z); if (i < NFFN) st128(&g_F[i * 512 + k * 32 + lane], z); spin(100); }
        __syncwarp();
        if (lane == 0) mbar_arrive(BAR(B_CLR2));
        TS(44);
        mbar_wait_n(BAR(B_MOD), 2);
        float d[4] = {0.f, 0.f, 0.f, 0.f};
        gemv_512x16(d, sb + OFF_Z, sb + OFF_S, 0, 16, lane);
        __syncwarp();
        if (lane == 0) mbar_arrive(BAR(B_ZFREE));
        if ((lane & 3) < 2) put4(&g_M[i * 16 + (lane >> 2) * 2 + (lane & 3)], d[0], d[1], d[2], d[3], tag);
        __syncwarp();
        if (lane == 0 && i >= 32 && i < 96) red_cnt(&g_sync[4 * 32 + 2]);
        TS(42);
        {
            const float4 v = get4(&g_M[((lane >> 2) & 1) * 3 * 512 + i * 4 + (lane & 3)], lane < 8, tag);
            if (lane < 8) stsf4(MISC + 96 + lane * 16, v);
        }
        __syncwarp();
        if (lane == 0) {
            if (i < NFFN) {
                wait_cnt(&g_sync[4 * 32 + 2], (ep + 1u) * 64u);
                mbar_wait(BAR(B_KV0FREE));
                asm volatile("fence.proxy.async.global;" ::: "memory");
                mbar_expect_tx(BAR(B_MODV), 16384);
                asm volatile("cp.async.bulk.shared::cluster.global.mbarrier::complete_tx::bytes [%0], [%1], %2, [%3];"
                             ::"r"(sb + OFF_SBCB), "l"(&g_M[512]), "r"(16384), "r"(BAR(B_MODV)) : "memory");
            } else {
                mbar_arrive(BAR(B_MODV));
            }
            TS(45);
        }
    } else {
        constexpr uint32_t ACT = SB + OFF_ACT, ACTB = SB + OFF_ACT + 1152, RED = SB + OFF_RED;
        const int g = lane >> 2, q = lane & 3;
        const int vrr = (lane & 15) >> 1, vb0 = (lane & 1) * 2;
        uint32_t cw[4];
        uint4 xv[2];
        uint32_t xh[4];
        TS0(32);
        {
            const uint4* xp = reinterpret_cast<const uint4*>(p.x + (warp & 3) * 512 + lane * 16);
            xv[0] = ldnc128_if(xp, warp < 4);
            xv[1] = ldnc128_if(xp + 1, warp < 4);
            const __nv_bfloat16* xq = p.x + vb0 * 512 + jj * 128 + warp * 16 + vrr;
            xh[0] = ldnc16(xq); xh[1] = ldnc16(xq + 512); xh[2] = ldnc16(xq + 8); xh[3] = ldnc16(xq + 520);
        }
#pragma unroll
        for (int b = 0; b < 4; b++) cw[b] = ldnc32(p.c + b * 512 + 2 * t);
        if (lane == 0) {
#pragma unroll
            for (int k = 0; k < 5; k++) {
                int idx = 4 + warp * 5 + k;
                if (idx >= B_YFREE) idx = (idx == 39) ? B_ZFREE : (idx == 40 ? B_P3 : (idx == 41 ? B_CLR2 : B_MODV));
                mbar_init(BAR(0) + idx * 8, 1);
            }
            asm volatile("fence.mbarrier_init.release.cluster;" ::: "memory");
        }
        __syncwarp();
        asm volatile("bar.arrive 5, 320;" ::: "memory");
        asm volatile("bar.arrive 6, 288;" ::: "memory");
        TS(48 + warp);
        asm volatile("bar.sync 4, 320;" ::: "memory");
        TS0(29);

#pragma unroll
        for (int b = 0; b < 4; b++) {
            const float c0 = bf_lo(cw[b]), c1 = bf_hi(cw[b]);
            sts32(sb + OFF_S + b * 1040 + t * 4, pack_bf16(__fdividef(c0, 1.f + __expf(-c0)), __fdividef(c1, 1.f + __expf(-c1))));
        }
        if (warp < 4) {
            const uint32_t u[8] = {xv[0].x, xv[0].y, xv[0].z, xv[0].w, xv[1].x, xv[1].y, xv[1].z, xv[1].w};
            float s = 0.f, ss = 0.f;
#pragma unroll
            for (int k = 0; k < 8; k++) s += bf_lo(u[k]) + bf_hi(u[k]);
#pragma unroll
            for (int o = 16; o; o >>= 1) s += __shfl_xor_sync(~0u, s, o);
            const float mean = s * (1.f / 512.f);
#pragma unroll
            for (int k = 0; k < 8; k++) { const float d0 = bf_lo(u[k]) - mean, d1 = bf_hi(u[k]) - mean; ss += d0 * d0 + d1 * d1; }
#pragma unroll
            for (int o = 16; o; o >>= 1) ss += __shfl_xor_sync(~0u, ss, o);
            if (lane == 0) { stsf(MISC + warp * 8, mean); stsf(MISC + warp * 8 + 4, rsqrtf(ss * (1.f / 512.f) + 1e-5f)); }
        }
        bar_main();
        mbar_wait(BAR(B_EP));
        const unsigned int ep = lds32(MISC + 224);
        const uint32_t tag = 1u + 2u * (ep & 1u);
        if (warp < 2) {
            mbar_wait(BAR(B_WA));
            TS0(26);
            float d[4] = {0.f, 0.f, 0.f, 0.f};
            gemv_512x16(d, sb + OFF_Z + warp * 4096 - jj * 4096, sb + OFF_S, jj * 128, 4, lane);
            if (q < 2) put4(&g_H[i * 32 + warp * 16 + g * 2 + q], d[0], d[1], d[2], d[3], tag);
        }
        TS0(1);
        mbar_wait_n(BAR(B_WQ), 4);
        TS0(3);
        {
            const float4 a = get4sum4(&g_H[(4 * (8 * jj + warp)) * 32 + lane], 32, tag);
            const float cx = __shfl_down_sync(~0u, a.x, 16), cy = __shfl_down_sync(~0u, a.y, 16);
            const float cz = __shfl_down_sync(~0u, a.z, 16), cwv = __shfl_down_sync(~0u, a.w, 16);
            if (lane < 16) {
                const float2 s0 = ldsf2(MISC + vb0 * 8), s1 = ldsf2(MISC + vb0 * 8 + 8);
                sts_frag(ACT, 272, warp * 16 + vrr, vb0,
                         (__uint_as_float(xh[0] << 16) - s0.x) * s0.y * (1.f + cx) + a.x,
                         (__uint_as_float(xh[1] << 16) - s1.x) * s1.y * (1.f + cy) + a.y,
                         (__uint_as_float(xh[2] << 16) - s0.x) * s0.y * (1.f + cz) + a.z,
                         (__uint_as_float(xh[3] << 16) - s1.x) * s1.y * (1.f + cwv) + a.w);
            }
        }
        bar_main();
        TS0(2);
        gemv_y_put(&g_Q[i * 128], ACT, tag);
        __syncwarp();
        if (lane == 0) mbar_arrive(BAR(B_YFREE));
        mbar_wait_n(BAR(B_WUK), 4);
        TS0(5);
        if (warp < 4) {
            const float4 a = get4sum4(&g_Q[hh * 4 * 128 + t], 128, tag);
            sts_frag(ACTB, 272, (t >> 4) * 16 + vrr, vb0, a.x, a.y, a.z, a.w);
        }
        bar_main();
        TS0(4);
        {
            float d[4] = {0.f, 0.f, 0.f, 0.f};
            const int blk = lane >> 3, r8 = lane & 7;
            const uint32_t arow = sb + OFF_X + (warp * 16 + (blk & 1) * 8 + r8) * 128;
            const uint32_t brow = ACTB + (r8 & 3) * 272 + blk * 16;
#pragma unroll
            for (int k2 = 0; k2 < 4; k2++) {
                uint32_t b[4], a0[4], a1[4];
                const uint32_t hb = arow + (k2 >> 1) * 16384;
                const int c0 = (k2 & 1) * 4 + (blk >> 1);
                ldsm4(b, brow + k2 * 64);
                ldsm4(a0, hb + ((c0 ^ r8) << 4));
                ldsm4(a1, hb + (((c0 + 2) ^ r8) << 4));
                mma16816(d, a0, b[0], b[1]);
                mma16816(d, a1, b[2], b[3]);
            }
            const float sc = 0.08838834764831845f * 1.4426950408889634f;
            if (q < 2) sts_frag(RED, 256, warp * 16 + g, 2 * q, d[0] * sc, d[1] * sc, d[2] * sc, d[3] * sc);
            fence_async_smem();
            bar_main();
            if (t == 0) {
#pragma unroll 1
                for (int b = 0; b < 4; b++) bulk_s2g(&g_qabs[(b * 32 + hh) * 512 + jj * 128], RED + b * 256, 256);
                asm volatile("cp.async.bulk.commit_group;" ::: "memory");
                asm volatile("cp.async.bulk.wait_group 0;" ::: "memory");
                red_cnt(&g_sync[4 * 32 + 1]);
                mbar_arrive(BAR(B_P3));
            }
            TS0(6);
        }
        const int wg = warp >> 2, wq = warp & 3;
        {
            constexpr uint32_t MX = RED;
            constexpr uint32_t LRED = RED + 512;
            constexpr uint32_t ALPHA = RED + 1536, MRUN = RED + 1664;
            float o[4][16];
            float lsum[8];
#pragma unroll
            for (int k = 0; k < 8; k++) lsum[k] = 0.f;
            if (t < 32) stsf(MRUN + t * 4, -INFINITY);
            mbar_wait(BAR(B_QABS));
            TS0(7);
#pragma unroll 1
            for (int tile = 0; tile < 2; tile++) {
                if (wg == tile) {
                    float s[16];
                    uint32_t da = desc_lo(SB + OFF_KV) + tile * (65536 >> 4), db = desc_lo(SB + OFF_X);
#pragma unroll 1
                    for (int cb = 0; cb < 8; cb++) {
                        mbar_wait(BAR(B_KV) + (tile * 8 + cb) * 8);
                        wg_fence();
#pragma unroll
                        for (int k = 0; k < 4; k++) wgmma_n32<0>(s, da + k * 2, db + k * 2, (cb | k) != 0);
                        wg_commit();
                        da += 8192 >> 4;
                        db += 4096 >> 4;
                    }
                    wg_wait0();
                    reg_fence(s);
                    if (tile == 1) { __syncwarp(); if (lane == 0) mbar_arrive(BAR(B_XFREE)); }
                    if (wq == 0) TS(8 + tile * 2);
                    float m[8];
#pragma unroll
                    for (int jb = 0; jb < 4; jb++) {
                        m[2 * jb] = fmaxf(s[4 * jb], s[4 * jb + 2]);
                        m[2 * jb + 1] = fmaxf(s[4 * jb + 1], s[4 * jb + 3]);
                    }
#pragma unroll
                    for (int of = 4; of <= 16; of <<= 1) {
#pragma unroll
                        for (int k = 0; k < 8; k++) m[k] = fmaxf(m[k], __shfl_xor_sync(~0u, m[k], of));
                    }
                    if (g == 0) {
#pragma unroll
                        for (int jb = 0; jb < 4; jb++)
                            asm volatile("st.shared.v2.f32 [%0], {%1,%2};" ::"r"(MX + (wq * 32 + 8 * jb + 2 * q) * 4), "f"(m[2 * jb]), "f"(m[2 * jb + 1]) : "memory");
                    }
                    if (tile == 0) asm volatile("bar.sync 2, 128;" ::: "memory"); else asm volatile("bar.sync 3, 128;" ::: "memory");
                    const float mold = ldsf(MRUN + tile * 128 + lane * 4);
                    const float mnew = fmaxf(fmaxf(fmaxf(ldsf(MX + lane * 4), ldsf(MX + 128 + lane * 4)), fmaxf(ldsf(MX + 256 + lane * 4), ldsf(MX + 384 + lane * 4))), mold);
                    uint32_t lo[4], hi[4];
#pragma unroll
                    for (int jb = 0; jb < 4; jb++) {
                        const float m0 = __shfl_sync(~0u, mnew, 8 * jb + 2 * q), m1 = __shfl_sync(~0u, mnew, 8 * jb + 2 * q + 1);
                        lo[jb] = pack_bf16(ex2(s[4 * jb] - m0), ex2(s[4 * jb + 1] - m1));
                        hi[jb] = pack_bf16(ex2(s[4 * jb + 2] - m0), ex2(s[4 * jb + 3] - m1));
                        lsum[2 * jb] = bf_lo(lo[jb]) + bf_lo(hi[jb]);
                        lsum[2 * jb + 1] = bf_hi(lo[jb]) + bf_hi(hi[jb]);
                    }
                    const uint32_t prow = sb + OFF_P + tile * 4096 + lane * 128;
                    stsm4t(prow + (((2 * wq) ^ (lane & 7)) << 4), lo[0], lo[1], lo[2], lo[3]);
                    stsm4t(prow + (((2 * wq + 1) ^ (lane & 7)) << 4), hi[0], hi[1], hi[2], hi[3]);
                    fence_async_smem();
                    if (wq == 0) { stsf(ALPHA + lane * 4, ex2(mold - mnew)); stsf(MRUN + (tile + 1) * 128 + lane * 4, mnew); }
                }
                bar_main();
                TS0(27 + tile);
                if (tile == 1) {
#pragma unroll
                    for (int jb = 0; jb < 4; jb++) {
                        const float2 a = ldsf2(ALPHA + (8 * jb + 2 * q) * 4);
#pragma unroll
                        for (int mt = 0; mt < 4; mt++) { o[mt][4 * jb] *= a.x; o[mt][4 * jb + 1] *= a.y; o[mt][4 * jb + 2] *= a.x; o[mt][4 * jb + 3] *= a.y; }
                    }
                }
                {
                    const uint32_t da = desc_lo(SB + OFF_KV) + tile * (65536 >> 4) + wg * (32768 >> 4), db = desc_lo(SB + OFF_P) + tile * (4096 >> 4);
                    wg_fence();
#pragma unroll
                    for (int k = 0; k < 4; k++) {
#pragma unroll
                        for (int mt = 0; mt < 4; mt++)
                            wgmma_n32<1>(o[mt], da + mt * (8192 >> 4) + k * (2048 >> 4), db + k * 2, tile | k);
                    }
                    wg_commit();
                }
                if (wg == tile) {
#pragma unroll
                    for (int of = 4; of <= 16; of <<= 1) {
#pragma unroll
                        for (int k = 0; k < 8; k++) lsum[k] += __shfl_xor_sync(~0u, lsum[k], of);
                    }
                    if (g == 0) {
#pragma unroll
                        for (int jb = 0; jb < 4; jb++)
                            asm volatile("st.shared.v2.f32 [%0], {%1,%2};" ::"r"(LRED + (warp * 32 + 8 * jb + 2 * q) * 4), "f"(lsum[2 * jb]), "f"(lsum[2 * jb + 1]) : "memory");
                    }
                    if (tile == 1) {
                        asm volatile("bar.sync 3, 128;" ::: "memory");
                        if (wq == 0) {
                            float l0 = 0.f, l1 = 0.f;
#pragma unroll
                            for (int w = 0; w < 4; w++) { l0 += ldsf(LRED + (w * 32 + lane) * 4); l1 += ldsf(LRED + ((w + 4) * 32 + lane) * 4); }
                            const float l = l0 * ldsf(ALPHA + lane * 4) + l1;
                            const float mf = ldsf(MRUN + 256 + lane * 4);
                            const float ln = __shfl_down_sync(~0u, l, 1), mn = __shfl_down_sync(~0u, mf, 1);
                            if ((lane & 1) == 0) put4(&g_stat[((lane >> 2) * 128 + i) * 2 + ((lane >> 1) & 1)], mf, l, mn, ln, tag);
                        }
                    }
                }
                wg_wait0();
#pragma unroll
                for (int mt = 0; mt < 4; mt++) reg_fence(o[mt]);
                if (tile == 0) { __syncwarp(); if (lane == 0) mbar_arrive(BAR(B_KV0FREE)); }
                TS0(9 + tile * 2);
            }
            const uint32_t keep = (g == 0) ? 0xFFFEFFFEu : 0xFFFFFFFFu;
            const uint32_t tg = (g == 0) ? ((ep & 1u) ? 0u : 0x00010001u) : 0u;
#pragma unroll
            for (int mt = 0; mt < 4; mt++) {
                uint32_t lo[4], hi[4];
#pragma unroll
                for (int jb = 0; jb < 4; jb++) {
                    lo[jb] = (pack_bf16(o[mt][4 * jb], o[mt][4 * jb + 1]) & keep) | tg;
                    hi[jb] = (pack_bf16(o[mt][4 * jb + 2], o[mt][4 * jb + 3]) & keep) | tg;
                }
                const uint32_t row = sb + OFF_STG + (wg * 2 + (mt >> 1)) * 8192 + lane * 256;
                const int ch = (mt & 1) * 8 + wq * 2;
                stsm4t(row + ((ch ^ (lane & 7)) << 4), lo[0], lo[1], lo[2], lo[3]);
                stsm4t(row + (((ch + 1) ^ (lane & 7)) << 4), hi[0], hi[1], hi[2], hi[3]);
            }
            fence_async_smem();
            if (wg == 0) asm volatile("bar.sync 2, 128;" ::: "memory"); else asm volatile("bar.sync 3, 128;" ::: "memory");
            if (warp == 4) TS(47);
            if (wq == 0 && lane == 0) {
                bulk_s2g(&g_part[i * 2048 + wg * 1024], sb + OFF_STG + wg * 16384, 16384);
                asm volatile("cp.async.bulk.commit_group;" ::: "memory");
                asm volatile("cp.async.bulk.wait_group 0;" ::: "memory");
                if (atomicAdd(reinterpret_cast<unsigned int*>(smem + OFF_MISC + 236), 1u) == 1u) red_cnt(&g_sync[bb * 32 + 1]);
            }
            TS0(12);
            if (warp == 4) TS(46);
        }
        mbar_wait(BAR(B_CLR2));
        TS0(15);
        constexpr uint32_t SCR = SB + OFF_SCR;
        {
            constexpr uint32_t CS = SB + OFF_P;
            const int b = warp >> 1;
            const uint32_t ptag = (ep & 1u) ? 0u : 1u;
            const int pi = lane >> 4, v = lane & 15;
            const uint4* sp = &g_stat[((hh >> 2) * 128 + b * 32 + lane) * 2 + ((hh >> 1) & 1)];
            const uint4* src = &g_part[((b * 32 + (warp & 1) * 16 + pi) * 4 + jj) * 512 + hh * 16 + v];
            float acc[8];
            int it = 0;
            bool ok;
            TS0(62);
            if (warp == 0) {
                const unsigned int target = (ep + 1u) * 32u;
#pragma unroll 1
                while (!__all_sync(~0u, (int)(ld_cnt(&g_sync[(lane & 3) * 32 + 1]) - target) >= 0) && ++it < SPIN_LIMIT) {}
                it = 0;
            }
            mbar_wait_n(BAR(B_WUV), 4);
            bar_main();
            TS0(13);
#pragma unroll 1
            do {
                const uint4 su = ld128(sp);
                uint4 r[8];
#pragma unroll
                for (int k = 0; k < 8; k++) r[k] = ld128(src + (size_t)k * 2 * 2048);
                ok = (su.x & 3u) == tag;
                const float mi = (hh & 1) ? __uint_as_float(su.z) : __uint_as_float(su.x & ~3u), li = (hh & 1) ? __uint_as_float(su.w) : __uint_as_float(su.y);
                float mx = mi;
#pragma unroll
                for (int of = 16; of; of >>= 1) mx = fmaxf(mx, __shfl_xor_sync(~0u, mx, of));
                float wi = ex2(mi - mx);
                float L = wi * li;
#pragma unroll
                for (int of = 16; of; of >>= 1) L += __shfl_xor_sync(~0u, L, of);
                wi = __fdividef(wi, L);
#pragma unroll
                for (int k = 0; k < 8; k++) acc[k] = 0.f;
#pragma unroll
                for (int k = 0; k < 8; k++) {
                    const float w = __shfl_sync(~0u, wi, (warp & 1) * 16 + 2 * k + pi);
                    ok = ok & ((r[k].x & 1u) == ptag);
                    acc[0] += w * bf_lo(r[k].x); acc[1] += w * bf_hi(r[k].x);
                    acc[2] += w * bf_lo(r[k].y); acc[3] += w * bf_hi(r[k].y);
                    acc[4] += w * bf_lo(r[k].z); acc[5] += w * bf_hi(r[k].z);
                    acc[6] += w * bf_lo(r[k].w); acc[7] += w * bf_hi(r[k].w);
                }
            } while (!__all_sync(~0u, ok) && ++it < SPIN_LIMIT);
#pragma unroll
            for (int k = 0; k < 8; k++) acc[k] += __shfl_xor_sync(~0u, acc[k], 16);
            const int ch = v ^ (hh & 7);
            if (pi == 0) {
                stsf4(CS + warp * 512 + ch * 32, make_float4(acc[0], acc[1], acc[2], acc[3]));
                stsf4(CS + warp * 512 + ch * 32 + 16, make_float4(acc[4], acc[5], acc[6], acc[7]));
            }
            bar_main();
            {
                const int b2 = t >> 6, c2 = (t & 63) * 2;
                const float2 u0 = ldsf2(CS + (2 * b2) * 512 + c2 * 4), u1 = ldsf2(CS + (2 * b2 + 1) * 512 + c2 * 4);
                sts32(ACT + b2 * 272 + c2 * 2, pack_bf16(u0.x + u1.x, u0.y + u1.y));
            }
            bar_main();
            TS0(14);
        }
        gemv_y_put(&g_C[i * 128], ACT, tag);
        mbar_wait_n(BAR(B_WO), 4);
        TS0(17);
        if (warp == 0) {
            const float4 a = get4sum4(&g_C[hh * 4 * 128 + jj * 32 + lane], 128, tag);
            sts_frag(ACTB, 80, (t >> 4) * 16 + vrr, vb0, a.x, a.y, a.z, a.w);
        }
        bar_main();
        TS0(16);
        {
            const int blk = lane >> 3, r8 = lane & 7;
            uint32_t b[4];
            ldsm4(b, ACTB + (r8 & 3) * 80 + blk * 16);
            const uint32_t wb = sb + OFF_X + warp * 4096 + ((blk >> 1) * 8 + r8) * 128;
#pragma unroll
            for (int mt = 0; mt < 4; mt++) {
                float d[4] = {0.f, 0.f, 0.f, 0.f};
                uint32_t a0[4], a1[4];
                const uint32_t co = ((2 * mt + (blk & 1)) ^ r8) << 4;
                ldsm4t(a0, wb + co);
                ldsm4t(a1, wb + 16 * 128 + co);
                mma16816(d, a0, b[0], b[1]);
                mma16816(d, a1, b[2], b[3]);
                if (q < 2) put4(&g_O[i * 512 + (warp * 4 + mt) * 16 + g * 2 + q], d[0], d[1], d[2], d[3], tag);
            }
            TS0(18);
        }
        const int V = i * 4 + (t & 3);
        const int vm = (V >> 4) * 16 + ((V & 15) >> 1), vb = (V & 1) * 2;
        float4 x1 = make_float4(0.f, 0.f, 0.f, 0.f);
        {
            mbar_wait(BAR(B_MODV));
            if (i < NFFN) mbar_wait_n(BAR(B_W1), 4);
            TS0(21);
            const float4 r = reduce16(g_O, 128, tag);
            if (t < 4) {
                const float4 x0 = ldsf4(MISC + 32 + t * 16), ga = ldsf4(MISC + 96 + t * 16);
                x1 = make_float4(x0.x + ga.x * r.x, x0.y + ga.y * r.y, x0.z + ga.z * r.z, x0.w + ga.w * r.w);
                put4(&g_X1[i * 8 + t], x1.x, x1.y, x1.z, x1.w, tag);
            }
            TS0(19);
        }
        if (i < NFFN) {
            float4 mv[4];
#pragma unroll
            for (int k = 0; k < 4; k++) {
                uint4 u = lds128(sb + OFF_SBCB + (t + 256 * k) * 16);
                int it = 0;
                while ((u.x & 3u) != tag && ++it < SPIN_LIMIT) u = ld128(&g_M[512 + t + 256 * k]);
                mv[k] = as_f4(u);
            }
            spin(HOPDELAY);
            uint4 ua, ub;
            {
                int it = 0;
                do { ua = ld128(&g_X1[(t >> 2) * 8 + (t & 3)]); ub = ld128(&g_X1[(t >> 2) * 8 + (t & 3) + 512]); } while (!__all_sync(~0u, (ua.x & 3u) == tag && (ub.x & 3u) == tag) && ++it < SPIN_LIMIT);
            }
            const float4 a = as_f4(ua), b = as_f4(ub);
            float s0 = (a.x + a.z) + (b.x + b.z), s1 = (a.y + a.w) + (b.y + b.w);
            float q0 = (a.x * a.x + a.z * a.z) + (b.x * b.x + b.z * b.z), q1 = (a.y * a.y + a.w * a.w) + (b.y * b.y + b.w * b.w);
#pragma unroll
            for (int of = 2; of <= 16; of <<= 1) {
                s0 += __shfl_xor_sync(~0u, s0, of); s1 += __shfl_xor_sync(~0u, s1, of);
                q0 += __shfl_xor_sync(~0u, q0, of); q1 += __shfl_xor_sync(~0u, q1, of);
            }
            constexpr uint32_t ST = SCR + 1024, ACT2 = SCR + 4096;
            if (lane < 2) stsf4(ST + (warp * 2 + lane) * 16, make_float4(s0, q0, s1, q1));
            bar_main();
            TS0(20);
            float4 tot = make_float4(0.f, 0.f, 0.f, 0.f);
#pragma unroll
            for (int w = 0; w < 8; w++) add4(tot, ldsf4(ST + (w * 2 + (t & 1)) * 16));
            const float mean0 = tot.x * (1.f / 512.f), mean1 = tot.z * (1.f / 512.f);
            const float r0 = rsqrtf(fmaxf(tot.y * (1.f / 512.f) - mean0 * mean0, 0.f) + 1e-5f);
            const float r1 = rsqrtf(fmaxf(tot.w * (1.f / 512.f) - mean1 * mean1, 0.f) + 1e-5f);
            const int m0 = (t >> 4) * 16 + vrr;
            sts_frag(ACT2, 1040, m0, vb0, (a.x - mean0) * r0 * (1.f + mv[2].x) + mv[0].x, (a.y - mean1) * r1 * (1.f + mv[2].y) + mv[0].y,
                     (a.z - mean0) * r0 * (1.f + mv[2].z) + mv[0].z, (a.w - mean1) * r1 * (1.f + mv[2].w) + mv[0].w);
            sts_frag(ACT2, 1040, m0 + 256, vb0, (b.x - mean0) * r0 * (1.f + mv[3].x) + mv[1].x, (b.y - mean1) * r1 * (1.f + mv[3].y) + mv[1].y,
                     (b.z - mean0) * r0 * (1.f + mv[3].z) + mv[1].z, (b.w - mean1) * r1 * (1.f + mv[3].w) + mv[1].w);
            bar_main();
            float d[4] = {0.f, 0.f, 0.f, 0.f};
            gemv_512x16(d, sb + OFF_Z, ACT2, warp * 64, 2, lane);
            constexpr uint32_t HR = SCR + 2048;
            if (q < 2) {
                const uint32_t a0 = HR + (warp * 64 + (2 * q) * 16 + g) * 4;
                stsf(a0, d[0]); stsf(a0 + 64, d[1]); stsf(a0 + 32, d[2]); stsf(a0 + 96, d[3]);
            }
            bar_main();
            float2 h0 = make_float2(0.f, 0.f), h1 = h0;
#pragma unroll
            for (int w = 0; w < 8; w++) {
                const float2 u = ldsf2(HR + (w * 64 + (g & 3) * 16 + 2 * q) * 4), v = ldsf2(HR + (w * 64 + (g & 3) * 16 + 2 * q + 8) * 4);
                h0.x += u.x; h0.y += u.y; h1.x += v.x; h1.y += v.y;
            }
            const uint32_t b0r = pack_bf16(fmaxf(h0.x, 0.f), fmaxf(h0.y, 0.f)), b1r = pack_bf16(fmaxf(h1.x, 0.f), fmaxf(h1.y, 0.f));
            TS0(22);
            const int blk = lane >> 3, r8 = lane & 7;
            const uint32_t wb = sb + OFF_W2 + warp * 2048 + ((blk >> 1) * 8 + r8) * 128;
#pragma unroll
            for (int mt = 0; mt < 4; mt++) {
                float e[4] = {0.f, 0.f, 0.f, 0.f};
                uint32_t a0[4];
                ldsm4t(a0, wb + (((2 * mt + (blk & 1)) ^ r8) << 4));
                mma16816(e, a0, b0r, b1r);
                if (q < 2) put4(&g_F[i * 512 + (warp * 4 + mt) * 16 + g * 2 + q], e[0], e[1], e[2], e[3], tag);
            }
            TS0(23);
        }
        {
            const float4 r = reduce16(g_F, NFFN, tag);
            if (t < 4) {
                const float4 gb = ldsf4(MISC + 96 + 64 + t * 16);
                p.out[vb * 512 + vm] = __float2bfloat16_rn(x1.x + gb.x * r.x);
                p.out[(vb + 1) * 512 + vm] = __float2bfloat16_rn(x1.y + gb.y * r.y);
                p.out[vb * 512 + vm + 8] = __float2bfloat16_rn(x1.z + gb.z * r.z);
                p.out[(vb + 1) * 512 + vm + 8] = __float2bfloat16_rn(x1.w + gb.w * r.w);
            }
            if (i == 0 && t < 5) g_sync[t * 32] = ep + 1u;
            TS0(24);
        }
    }
}

typedef CUresult (*EncodeFn)(CUtensorMap*, CUtensorMapDataType, cuuint32_t, void*, const cuuint64_t*, const cuuint64_t*, const cuuint32_t*,
                             const cuuint32_t*, CUtensorMapInterleave, CUtensorMapSwizzle, CUtensorMapL2promotion, CUtensorMapFloatOOBfill);

void make_map(EncodeFn enc, CUtensorMap* m, const void* base, int rank, const cuuint64_t* dims, const cuuint64_t* strides, const cuuint32_t* box,
              CUtensorMapSwizzle sw) {
    cuuint32_t es[3] = {1, 1, 1};
    CUresult r = enc(m, CU_TENSOR_MAP_DATA_TYPE_BFLOAT16, rank, const_cast<void*>(base), dims, strides, box, es, CU_TENSOR_MAP_INTERLEAVE_NONE, sw,
                     CU_TENSOR_MAP_L2_PROMOTION_NONE, CU_TENSOR_MAP_FLOAT_OOB_FILL_NONE);
    if (r != CUDA_SUCCESS) fprintf(stderr, "cuTensorMapEncodeTiled failed: %d\n", (int)r);
}
void map2d(EncodeFn enc, CUtensorMap* m, const void* base, uint64_t rows, uint64_t cols, uint32_t boxr, uint32_t boxc, CUtensorMapSwizzle sw) {
    cuuint64_t dims[2] = {cols, rows};
    cuuint64_t strides[1] = {cols * 2};
    cuuint32_t box[2] = {boxc, boxr};
    make_map(enc, m, base, 2, dims, strides, box, sw);
}
void map3d(EncodeFn enc, CUtensorMap* m, const void* base, uint64_t rows, uint32_t boxr, uint32_t boxb) {
    cuuint64_t dims[3] = {64, rows, 8};
    cuuint64_t strides[2] = {1024, 128};
    cuuint32_t box[3] = {64, boxr, boxb};
    make_map(enc, m, base, 3, dims, strides, box, CU_TENSOR_MAP_SWIZZLE_128B);
}

}

extern "C" void kernel_launch(void* const* d_in, const int* in_sizes, int n_in, void* d_out, int out_size) {
    (void)in_sizes; (void)n_in; (void)out_size;
    static EncodeFn enc = nullptr;
    static void* qabs_ptr = nullptr;
    if (!enc) {
        void* fn = nullptr;
        cudaDriverEntryPointQueryResult st;
        cudaGetDriverEntryPoint("cuTensorMapEncodeTiled", &fn, cudaEnableDefault, &st);
        enc = (EncodeFn)fn;
        cudaFuncSetAttribute(fused_kernel, cudaFuncAttributeMaxDynamicSharedMemorySize, SMEM_BYTES);
        cudaGetSymbolAddress(&qabs_ptr, g_qabs);
    }
    Params p;
    map2d(enc, &p.kv, d_in[1], 16384, 512, 64, 64, CU_TENSOR_MAP_SWIZZLE_128B);
    map2d(enc, &p.wq, d_in[2], 512, 4096, 64, 64, CU_TENSOR_MAP_SWIZZLE_128B);
    map2d(enc, &p.wuk, d_in[3], 512, 4096, 64, 64, CU_TENSOR_MAP_SWIZZLE_128B);
    map2d(enc, &p.wuv, d_in[4], 512, 4096, 64, 64, CU_TENSOR_MAP_SWIZZLE_128B);
    map3d(enc, &p.wo, d_in[5], 4096, 32, 2);
    map2d(enc, &p.w1, d_in[7], 512, 1376, 256, 16, CU_TENSOR_MAP_SWIZZLE_32B);
    map3d(enc, &p.w2, d_in[8], 1376, 16, 4);
    map2d(enc, &p.wmod, d_in[10], 512, 3072, 256, 16, CU_TENSOR_MAP_SWIZZLE_32B);
    map3d(enc, &p.qabs, qabs_ptr, 128, 32, 8);
    map2d(enc, &p.wmoda, d_in[10], 512, 3072, 128, 16, CU_TENSOR_MAP_SWIZZLE_32B);
    p.x = (const __nv_bfloat16*)d_in[0];
    p.c = (const __nv_bfloat16*)d_in[9];
    p.wmodp = (const __nv_bfloat16*)d_in[10];
    p.out = (__nv_bfloat16*)d_out;
    fused_kernel<<<NCTA, NTHREADS, SMEM_BYTES, cudaStreamPerThread>>>(p);
}
```

```cpp
#include <cuda_runtime.h>
#include <cuda_bf16.h>
#include <cuda.h>
#include <stdint.h>
#include <stdio.h>

namespace {

constexpr int NCTA = 128;
constexpr int NTHREADS = 320;
constexpr int NFFN = 86;
#define WINDOW 8
#define WINDOW_S WINDOW
#define WINDOW_T WINDOW
#define DT_F 350
#define DT_0 350
#define DT_S 330
#define DT_T 320
#define DT_T2 200
#define QK_EARLY 4
#define G5DELAY 150
#define G6ADELAY 250
#define FFNDELAY 2600
#define GATEDELAY 0
#define POLLGAP 0
#define HOPDELAY 300

constexpr uint32_t OFF_KV = 0;
constexpr uint32_t OFF_X = 131072;
constexpr uint32_t OFF_Y = 163840;
constexpr uint32_t OFF_Z = 196608;
constexpr uint32_t OFF_P = 212992;
constexpr uint32_t OFF_S = 221184;
constexpr uint32_t OFF_ACT = 225344;
constexpr uint32_t OFF_RED = 227648;
constexpr uint32_t OFF_BAR = 229696;
constexpr uint32_t OFF_MISC = 230208;
constexpr uint32_t SMEM_BYTES = 230720;
constexpr uint32_t OFF_STG = OFF_KV;
constexpr uint32_t OFF_XCH = OFF_KV + 16384;
constexpr uint32_t OFF_W2 = OFF_KV + 32768;
constexpr uint32_t OFF_SBCB = OFF_KV + 49152;
constexpr uint32_t OFF_SCR = OFF_KV + 65536;

enum {
    B_WQ = 0,
    B_WUK = 4,
    B_KV = 8,
    B_MOD = 24,
    B_WUV = 26,
    B_WO = 30,
    B_W1 = 34,
    B_W2 = 36,
    B_QABS = 38,
    B_YFREE = 39,
    B_XFREE = 40,
    B_ZFREE = 41,
    B_KV0FREE = 42,
    B_P3 = 43,
    B_CLR2 = 44,
    B_MODV = 45,
    B_WA = 46,
    B_EP = 47,
    B_PEER0 = 48,
    B_XCH = 49,
    B_G4 = 50,
    B_XST = 51,
    B_COUNT = 52
};

struct alignas(64) Params {
    CUtensorMap kv, wq, wuk, wuv, wo, w1, w2, wmod, qabs, wmoda;
    const __nv_bfloat16* x;
    const __nv_bfloat16* c;
    const __nv_bfloat16* wmodp;
    __nv_bfloat16* out;
};

__device__ uint4 g_H[128 * 32];
__device__ uint4 g_Q[128 * 128];
__device__ __nv_bfloat16 g_qabs[4 * 32 * 512];
__device__ uint4 g_part[128 * 4 * 16 * 16];
__device__ uint4 g_stat[8 * 64 * 2];
__device__ uint4 g_C[128 * 128];
__device__ uint4 g_O[128 * 512];
__device__ uint4 g_X1[128 * 8];
__device__ uint4 g_F[NFFN * 512];
__device__ uint4 g_M[4 * 512];
constexpr int NSYNC = 8;
__device__ __align__(128) unsigned int g_sync[NSYNC * 32];

__device__ __forceinline__ uint32_t smem_u32(const void* p) { return (uint32_t)__cvta_generic_to_shared(p); }
__device__ __forceinline__ void mbar_init(uint32_t bar, int cnt) { asm volatile("mbarrier.init.shared::cta.b64 [%0], %1;" ::"r"(bar), "r"(cnt) : "memory"); }
__device__ __forceinline__ void mbar_expect_tx(uint32_t bar, uint32_t bytes) { asm volatile("mbarrier.arrive.expect_tx.shared::cta.b64 _, [%0], %1;" ::"r"(bar), "r"(bytes) : "memory"); }
__device__ __forceinline__ void mbar_arrive(uint32_t bar) { asm volatile("mbarrier.arrive.shared::cta.b64 _, [%0];" ::"r"(bar) : "memory"); }
constexpr int SPIN_LIMIT = 1 << 20;
__device__ __forceinline__ void mbar_wait(uint32_t bar) {
    asm volatile("{\n.reg .pred p;\n.reg .u32 n;\nmov.u32 n, 0;\n"
                 "LW:\nmbarrier.try_wait.parity.shared::cta.b64 p, [%0], 0;\n@p bra LD;\n"
                 "add.u32 n, n, 1;\nsetp.lt.u32 p, n, 4194304;\n@p bra LW;\nLD:\n}" ::"r"(bar) : "memory");
}
__device__ __forceinline__ bool mbar_test(uint32_t bar) {
    uint32_t ok;
    asm volatile("{\n.reg .pred p;\nmbarrier.test_wait.parity.shared::cta.b64 p, [%1], 0;\nselp.u32 %0, 1, 0, p;\n}" : "=r"(ok) : "r"(bar) : "memory");
    return ok;
}
__device__ __forceinline__ void mbar_wait_n(uint32_t bar, int n) {
#pragma unroll 1
    for (int k = 0; k < n; k++) mbar_wait(bar + k * 8);
}
__device__ __forceinline__ void bar_main() { asm volatile("bar.sync 1, 256;" ::: "memory"); }
__device__ __forceinline__ void fence_async_smem() { asm volatile("fence.proxy.async.shared::cta;" ::: "memory"); }

__device__ __forceinline__ uint4 ld128(const uint4* p) {
    uint4 v;
    asm volatile("{\n.reg .b128 t;\n.reg .b64 lo, hi;\nld.relaxed.gpu.global.b128 t, [%4];\nmov.b128 {lo, hi}, t;\nmov.b64 {%0,%1}, lo;\nmov.b64 {%2,%3}, hi;\n}"
                 : "=r"(v.x), "=r"(v.y), "=r"(v.z), "=r"(v.w) : "l"(p) : "memory");
    return v;
}
__device__ __forceinline__ void st128(uint4* p, uint4 v) {
    asm volatile("{\n.reg .b128 t;\n.reg .b64 lo, hi;\nmov.b64 lo, {%1,%2};\nmov.b64 hi, {%3,%4};\nmov.b128 t, {lo, hi};\nst.relaxed.gpu.global.b128 [%0], t;\n}"
                 ::"l"(p), "r"(v.x), "r"(v.y), "r"(v.z), "r"(v.w) : "memory");
}
__device__ __forceinline__ uint4 ldnc128_if(const void* p, bool c) {
    uint4 v;
    asm volatile("{\n.reg .pred p;\nsetp.ne.u32 p, %5, 0;\nmov.u32 %0, 0;\nmov.u32 %1, 0;\nmov.u32 %2, 0;\nmov.u32 %3, 0;\n@p ld.global.nc.v4.u32 {%0,%1,%2,%3}, [%4];\n}"
                 : "=r"(v.x), "=r"(v.y), "=r"(v.z), "=r"(v.w) : "l"(p), "r"((uint32_t)c));
    return v;
}
__device__ __forceinline__ uint32_t ldnc32(const void* p) { uint32_t v; asm volatile("ld.global.nc.u32 %0, [%1];" : "=r"(v) : "l"(p)); return v; }
__device__ __forceinline__ uint32_t ldnc16(const void* p) { uint32_t v; asm volatile("ld.global.nc.u16 %0, [%1];" : "=r"(v) : "l"(p)); return v; }
__device__ __forceinline__ unsigned int ld_epoch(const unsigned int* p) { unsigned int v; asm volatile("ld.relaxed.gpu.global.u32 %0, [%1];" : "=r"(v) : "l"(p)); return v; }
__device__ __forceinline__ void put4(uint4* p, float a, float b, float c, float d, uint32_t tag) {
    st128(p, make_uint4((__float_as_uint(a) & ~3u) | tag, __float_as_uint(b), __float_as_uint(c), __float_as_uint(d)));
}
__device__ __forceinline__ float4 as_f4(uint4 v) {
    return make_float4(__uint_as_float(v.x & ~3u), __uint_as_float(v.y), __uint_as_float(v.z), __uint_as_float(v.w));
}
__device__ __forceinline__ void add4(float4& a, const float4& b) { a.x += b.x; a.y += b.y; a.z += b.z; a.w += b.w; }
__device__ __forceinline__ float4 get4(const uint4* p, bool act, uint32_t tag) {
    uint4 v = make_uint4(tag, 0, 0, 0);
    int it = 0;
#pragma unroll 1
    do { if (act) v = ld128(p); } while (!__all_sync(~0u, (v.x & 3u) == tag) && ++it < SPIN_LIMIT);
    return as_f4(v);
}
__device__ __forceinline__ float4 get4sum2(const uint4* p0, const uint4* p1, bool act1, uint32_t tag) {
    uint4 u, v = make_uint4(tag, 0, 0, 0);
    int it = 0;
#pragma unroll 1
    do { u = ld128(p0); if (act1) v = ld128(p1); } while (!__all_sync(~0u, (u.x & 3u) == tag && (v.x & 3u) == tag) && ++it < SPIN_LIMIT);
    float4 a = as_f4(u);
    add4(a, make_float4(__uint_as_float(v.x & ~3u), __uint_as_float(v.y), __uint_as_float(v.z), __uint_as_float(v.w)));
    return a;
}

__device__ __forceinline__ float4 get4sum4(const uint4* p0, int stride, uint32_t tag) {
    uint4 u0, u1, u2, u3;
    int it = 0;
#pragma unroll 1
    do { u0 = ld128(p0); u1 = ld128(p0 + stride); u2 = ld128(p0 + 2 * stride); u3 = ld128(p0 + 3 * stride); }
    while (!__all_sync(~0u, ((u0.x ^ tag) & 3u) == 0 && ((u1.x ^ tag) & 3u) == 0 && ((u2.x ^ tag) & 3u) == 0 && ((u3.x ^ tag) & 3u) == 0) && ++it < SPIN_LIMIT);
    float4 a = as_f4(u0), b = as_f4(u2);
    add4(a, as_f4(u1));
    add4(b, as_f4(u3));
    add4(a, b);
    return a;
}
__device__ __forceinline__ uint32_t pack_bf16(float lo, float hi) {
    uint32_t r;
    asm("cvt.rn.bf16x2.f32 %0, %1, %2;" : "=r"(r) : "f"(hi), "f"(lo));
    return r;
}
__device__ __forceinline__ float bf_lo(uint32_t u) { return __uint_as_float(u << 16); }
__device__ __forceinline__ float bf_hi(uint32_t u) { return __uint_as_float(u & 0xffff0000u); }
__device__ __forceinline__ float ex2(float x) { float y; asm("ex2.approx.ftz.f32 %0, %1;" : "=f"(y) : "f"(x)); return y; }

__device__ __forceinline__ void ldsm4(uint32_t (&r)[4], uint32_t addr) {
    asm volatile("ldmatrix.sync.aligned.m8n8.x4.shared.b16 {%0,%1,%2,%3}, [%4];" : "=r"(r[0]), "=r"(r[1]), "=r"(r[2]), "=r"(r[3]) : "r"(addr) : "memory");
}
__device__ __forceinline__ void ldsm4t(uint32_t (&r)[4], uint32_t addr) {
    asm volatile("ldmatrix.sync.aligned.m8n8.x4.trans.shared.b16 {%0,%1,%2,%3}, [%4];" : "=r"(r[0]), "=r"(r[1]), "=r"(r[2]), "=r"(r[3]) : "r"(addr) : "memory");
}
__device__ __forceinline__ void stsm4t(uint32_t addr, uint32_t r0, uint32_t r1, uint32_t r2, uint32_t r3) {
    asm volatile("stmatrix.sync.aligned.m8n8.x4.trans.shared.b16 [%0], {%1,%2,%3,%4};" ::"r"(addr), "r"(r0), "r"(r1), "r"(r2), "r"(r3) : "memory");
}
__device__ __forceinline__ void mma16816(float (&d)[4], const uint32_t (&a)[4], uint32_t b0, uint32_t b1) {
    asm volatile("mma.sync.aligned.m16n8k16.row.col.f32.bf16.bf16.f32 {%0,%1,%2,%3}, {%4,%5,%6,%7}, {%8,%9}, {%0,%1,%2,%3};"
                 : "+f"(d[0]), "+f"(d[1]), "+f"(d[2]), "+f"(d[3]) : "r"(a[0]), "r"(a[1]), "r"(a[2]), "r"(a[3]), "r"(b0), "r"(b1));
}
__device__ __forceinline__ void sts32(uint32_t a, uint32_t v) { asm volatile("st.shared.b32 [%0], %1;" ::"r"(a), "r"(v) : "memory"); }
__device__ __forceinline__ void sts16(uint32_t a, float v) {
    __nv_bfloat16 h = __float2bfloat16_rn(v);
    asm volatile("st.shared.b16 [%0], %1;" ::"r"(a), "h"(*reinterpret_cast<unsigned short*>(&h)) : "memory");
}
__device__ __forceinline__ void stsf(uint32_t a, float v) { asm volatile("st.shared.f32 [%0], %1;" ::"r"(a), "f"(v) : "memory"); }
__device__ __forceinline__ void stsf4(uint32_t a, float4 v) { asm volatile("st.shared.v4.f32 [%0], {%1,%2,%3,%4};" ::"r"(a), "f"(v.x), "f"(v.y), "f"(v.z), "f"(v.w) : "memory"); }
__device__ __forceinline__ uint32_t lds32(uint32_t a) { uint32_t v; asm volatile("ld.shared.b32 %0, [%1];" : "=r"(v) : "r"(a) : "memory"); return v; }
__device__ __forceinline__ float ldsf(uint32_t a) { float v; asm volatile("ld.shared.f32 %0, [%1];" : "=f"(v) : "r"(a) : "memory"); return v; }
__device__ __forceinline__ float2 ldsf2(uint32_t a) { float2 v; asm volatile("ld.shared.v2.f32 {%0,%1}, [%2];" : "=f"(v.x), "=f"(v.y) : "r"(a) : "memory"); return v; }
__device__ __forceinline__ float4 ldsf4(uint32_t a) { float4 v; asm volatile("ld.shared.v4.f32 {%0,%1,%2,%3}, [%4];" : "=f"(v.x), "=f"(v.y), "=f"(v.z), "=f"(v.w) : "r"(a) : "memory"); return v; }
__device__ __forceinline__ uint4 lds128(uint32_t a) { uint4 v; asm volatile("ld.shared.v4.b32 {%0,%1,%2,%3}, [%4];" : "=r"(v.x), "=r"(v.y), "=r"(v.z), "=r"(v.w) : "r"(a) : "memory"); return v; }

__device__ __forceinline__ void tma2d(uint32_t dst, const CUtensorMap* m, int c0, int c1, uint32_t bar, uint32_t bytes, uint64_t pol) {
    asm volatile("{\n.reg .pred p;\nelect.sync _|p, 0xffffffff;\n"
                 "@p mbarrier.arrive.expect_tx.shared::cta.b64 _, [%2], %6;\n"
                 "@p cp.async.bulk.tensor.2d.shared::cluster.global.mbarrier::complete_tx::bytes.L2::cache_hint [%0], [%1, {%3, %4}], [%2], %5;\n}"
                 ::"r"(dst), "l"(m), "r"(bar), "r"(c0), "r"(c1), "l"(pol), "r"(bytes) : "memory");
}
__device__ __forceinline__ void tma3d(uint32_t dst, const CUtensorMap* m, int c0, int c1, int c2, uint32_t bar, uint32_t bytes, uint64_t pol) {
    asm volatile("{\n.reg .pred p;\nelect.sync _|p, 0xffffffff;\n"
                 "@p mbarrier.arrive.expect_tx.shared::cta.b64 _, [%2], %7;\n"
                 "@p cp.async.bulk.tensor.3d.shared::cluster.global.mbarrier::complete_tx::bytes.L2::cache_hint [%0], [%1, {%3, %4, %5}], [%2], %6;\n}"
                 ::"r"(dst), "l"(m), "r"(bar), "r"(c0), "r"(c1), "r"(c2), "l"(pol), "r"(bytes) : "memory");
}
__device__ __forceinline__ void tma2d_na(uint32_t dst, const CUtensorMap* m, int c0, int c1, uint32_t bar, uint64_t pol) {
    asm volatile("{\n.reg .pred p;\nelect.sync _|p, 0xffffffff;\n"
                 "@p cp.async.bulk.tensor.2d.shared::cluster.global.mbarrier::complete_tx::bytes.L2::cache_hint [%0], [%1, {%3, %4}], [%2], %5;\n}"
                 ::"r"(dst), "l"(m), "r"(bar), "r"(c0), "r"(c1), "l"(pol) : "memory");
}
__device__ __forceinline__ uint32_t mapa(uint32_t addr, uint32_t rank) {
    uint32_t r;
    asm("mapa.shared::cluster.u32 %0, %1, %2;" : "=r"(r) : "r"(addr), "r"(rank));
    return r;
}
__device__ __forceinline__ void st_async4(uint32_t raddr, uint32_t a, uint32_t b, uint32_t c, uint32_t d, uint32_t rbar) {
    asm volatile("st.async.weak.shared::cluster.mbarrier::complete_tx::bytes.v4.b32 [%0], {%1,%2,%3,%4}, [%5];" ::"r"(raddr), "r"(a), "r"(b), "r"(c), "r"(d), "r"(rbar) : "memory");
}
__device__ __forceinline__ void st_async2(uint32_t raddr, float a, float b, uint32_t rbar) {
    asm volatile("st.async.weak.shared::cluster.mbarrier::complete_tx::bytes.v2.f32 [%0], {%1,%2}, [%3];" ::"r"(raddr), "f"(a), "f"(b), "r"(rbar) : "memory");
}
__device__ __forceinline__ void tma3d_mc(uint32_t dst, const CUtensorMap* m, int c0, int c1, int c2, uint32_t bar, uint32_t bytes) {
    asm volatile("{\n.reg .pred p;\nelect.sync _|p, 0xffffffff;\n"
                 "@p mbarrier.arrive.expect_tx.shared::cta.b64 _, [%2], %6;\n"
                 "@p cp.async.bulk.tensor.3d.shared::cluster.global.mbarrier::complete_tx::bytes.multicast::cluster [%0], [%1, {%3, %4, %5}], [%2], %7;\n}"
                 ::"r"(dst), "l"(m), "r"(bar), "r"(c0), "r"(c1), "r"(c2), "r"(bytes), "h"((unsigned short)3) : "memory");
}
__device__ __forceinline__ void bulk_s2g(void* dst, uint32_t src, uint32_t bytes) {
    asm volatile("cp.async.bulk.global.shared::cta.bulk_group [%0], [%1], %2;" ::"l"(dst), "r"(src), "r"(bytes) : "memory");
}
__device__ __forceinline__ void prefetch_map(const CUtensorMap* m) { asm volatile("prefetch.tensormap [%0];" ::"l"(m) : "memory"); }

constexpr uint32_t DESC_HI = 64u | (1u << 30);
__device__ __forceinline__ constexpr uint32_t desc_lo(uint32_t addr) { return ((addr & 0x3FFFF) >> 4) | (1u << 16); }
__device__ __forceinline__ void wg_fence() { asm volatile("wgmma.fence.sync.aligned;" ::: "memory"); }
__device__ __forceinline__ void wg_commit() { asm volatile("wgmma.commit_group.sync.aligned;" ::: "memory"); }
__device__ __forceinline__ void wg_wait0() { asm volatile("wgmma.wait_group.sync.aligned 0;" ::: "memory"); }
template <int TA>
__device__ __forceinline__ void wgmma_n32(float (&d)[16], uint32_t alo, uint32_t blo, int scale_d) {
    asm volatile("{\n.reg .pred p;\n.reg .b64 da, db;\nsetp.ne.b32 p, %18, 0;\nmov.b64 da, {%16, %20};\nmov.b64 db, {%17, %20};\n"
                 "wgmma.mma_async.sync.aligned.m64n32k16.f32.bf16.bf16 "
                 "{%0,%1,%2,%3,%4,%5,%6,%7,%8,%9,%10,%11,%12,%13,%14,%15}, da, db, p, 1, 1, %19, 0;\n}"
                 : "+f"(d[0]), "+f"(d[1]), "+f"(d[2]), "+f"(d[3]), "+f"(d[4]), "+f"(d[5]), "+f"(d[6]), "+f"(d[7]),
                   "+f"(d[8]), "+f"(d[9]), "+f"(d[10]), "+f"(d[11]), "+f"(d[12]), "+f"(d[13]), "+f"(d[14]), "+f"(d[15])
                 : "r"(alo), "r"(blo), "r"(scale_d), "n"(TA), "n"(DESC_HI));
}
template <int N>
__device__ __forceinline__ void reg_fence(float (&d)[N]) {
#pragma unroll
    for (int i = 0; i < N; i++) asm volatile("" : "+f"(d[i])::"memory");
}

#define TS(slot)
#define TS0(slot)

__device__ __forceinline__ unsigned int gtimer_lo() {
    unsigned long long t;
    asm volatile("mov.u64 %0, %globaltimer;" : "=l"(t));
    return (unsigned int)t;
}
__device__ __forceinline__ void spin(int cycles) {
    const unsigned int t0 = clock();
    while (clock() - t0 < (unsigned int)cycles) {}
}
__device__ __forceinline__ unsigned int ld_cnt(const unsigned int* p) {
    unsigned int v;
    asm volatile("ld.relaxed.gpu.global.u32 %0, [%1];" : "=r"(v) : "l"(p) : "memory");
    return v;
}
__device__ __forceinline__ void wait_cnt(const unsigned int* p, unsigned int target) {
    int it = 0;
#pragma unroll 1
    while ((int)(ld_cnt(p) - target) < 0) { if (++it > SPIN_LIMIT) break; }
}
__device__ __forceinline__ void red_cnt(unsigned int* p) { asm volatile("red.relaxed.gpu.global.add.u32 [%0], 1;" ::"l"(p) : "memory"); }

constexpr uint32_t SB0 = 1024;
__device__ __forceinline__ uint32_t smem_base() {
    extern __shared__ __align__(1024) uint8_t smem_dyn[];
    return smem_u32(smem_dyn);
}

__device__ __forceinline__ void gemv_y_put(uint4* dst, uint32_t act, uint32_t tag) {
    const int lane = threadIdx.x & 31, warp = threadIdx.x >> 5;
    const int blk = lane >> 3, r8 = lane & 7;
    const int ch = (warp & 3) * 2 + (blk & 1);
    const uint32_t arow = smem_base() + OFF_Y + (warp >> 2) * 16384 + ((blk >> 1) * 8 + r8) * 128 + ((ch ^ r8) << 4);
    const uint32_t brow = act + (r8 & 3) * 272 + blk * 16;
    uint32_t a[8][4], b[4][4];
#pragma unroll
    for (int k = 0; k < 8; k++) ldsm4t(a[k], arow + k * 16 * 128);
#pragma unroll
    for (int k = 0; k < 4; k++) ldsm4(b[k], brow + k * 64);
    float d[4] = {0.f, 0.f, 0.f, 0.f}, e[4] = {0.f, 0.f, 0.f, 0.f};
#pragma unroll
    for (int k = 0; k < 4; k++) {
        mma16816(d, a[2 * k], b[k][0], b[k][1]);
        mma16816(e, a[2 * k + 1], b[k][2], b[k][3]);
    }
    if ((lane & 3) < 2) put4(dst + warp * 16 + (lane >> 2) * 2 + (lane & 3), d[0] + e[0], d[1] + e[1], d[2] + e[2], d[3] + e[3], tag);
}

__device__ __forceinline__ void gemv_512x16(float (&d)[4], uint32_t tile, uint32_t act, int k0, int nk2, int lane) {
    const int blk = lane >> 3, r8 = lane & 7;
    uint32_t arow = tile + (k0 + (blk >> 1) * 8 + r8) * 32 + (((blk & 1) ^ ((r8 >> 2) & 1)) << 4);
    uint32_t brow = act + (r8 & 3) * 1040 + (k0 + blk * 8) * 2;
#pragma unroll 2
    for (int k2 = 0; k2 < nk2; k2++) {
        uint32_t b[4], a0[4], a1[4];
        ldsm4(b, brow);
        ldsm4t(a0, arow);
        ldsm4t(a1, arow + 512);
        mma16816(d, a0, b[0], b[1]);
        mma16816(d, a1, b[2], b[3]);
        brow += 64;
        arow += 1024;
    }
}

__device__ __noinline__ float4 reduce16(const uint4* base, int n, uint32_t tag, int delay) {
    const int t = threadIdx.x, lane = t & 31, warp = t >> 5;
    const uint32_t SCR = smem_base() + OFF_SCR;
    const int pp = t >> 2;
    const uint4* p0 = base + (size_t)pp * 512 + blockIdx.x * 4 + (t & 3);
    spin(delay);
    float4 a = get4sum2(p0, p0 + 64 * 512, pp + 64 < n, tag);
#pragma unroll
    for (int of = 4; of <= 16; of <<= 1) {
        a.x += __shfl_xor_sync(~0u, a.x, of); a.y += __shfl_xor_sync(~0u, a.y, of);
        a.z += __shfl_xor_sync(~0u, a.z, of); a.w += __shfl_xor_sync(~0u, a.w, of);
    }
    if (lane < 4) stsf4(SCR + (warp * 4 + lane) * 16, a);
    bar_main();
    float4 r = make_float4(0.f, 0.f, 0.f, 0.f);
    if (t < 4) {
#pragma unroll
        for (int w = 0; w < 8; w++) add4(r, ldsf4(SCR + (w * 4 + t) * 16));
    }
    return r;
}
__device__ __forceinline__ void sts_frag(uint32_t base, uint32_t stride, int m, int b0, float x, float y, float z, float w) {
    const uint32_t a = base + b0 * stride + m * 2;
    sts16(a, x); sts16(a + stride, y); sts16(a + 16, z); sts16(a + stride + 16, w);
}

__global__ void __cluster_dims__(2, 1, 1) __launch_bounds__(NTHREADS, 1) fused_kernel(const __grid_constant__ Params p) {
    extern __shared__ __align__(1024) uint8_t smem[];
    const uint32_t sb = smem_base();
    const int t = threadIdx.x, lane = t & 31;
    const int warp = __shfl_sync(0xffffffffu, t >> 5, 0);
    const int i = blockIdx.x;
    const int hh = i >> 2, jj = i & 3;
    const int bb = i >> 5, chunk = i & 31;
    const uint32_t rank = i & 1;
    auto BAR = [&](int k) { return sb + OFF_BAR + k * 8; };
    const uint32_t MISC = sb + OFF_MISC;

    if (warp == 8) {
        if (lane == 0) {
            TS(0);
            prefetch_map(&p.wmoda);
            prefetch_map(&p.wq);
            mbar_init(BAR(B_WA), 1);
            mbar_init(BAR(0), 1);
            asm volatile("fence.mbarrier_init.release.cluster;" ::: "memory");
            fence_async_smem();
            mbar_expect_tx(BAR(B_WA), 8192);
        }
        __syncwarp();
        uint64_t pol;
        asm volatile("createpolicy.fractional.L2::evict_first.b64 %0, 1.0;" : "=l"(pol));
        tma2d_na(sb + OFF_Z, &p.wmoda, 16 * hh, jj * 128, BAR(B_WA), pol);
        tma2d_na(sb + OFF_Z + 4096, &p.wmoda, 512 + 16 * hh, jj * 128, BAR(B_WA), pol);
        tma2d(sb + OFF_Y, &p.wq, hh * 128, jj * 128, BAR(0), 8192, pol);
        unsigned int due = gtimer_lo() + DT_0;
        TS(56);
        if (lane == 0) {
            if ((sb & 0xFFFFFFu) != SB0) __trap();
#pragma unroll
            for (int k = 1; k < 4; k++) mbar_init(BAR(k), 1);
            asm volatile("fence.mbarrier_init.release.cluster;" ::: "memory");
            fence_async_smem();
        }
        __syncwarp();
        asm volatile("bar.arrive 4, 320;" ::: "memory");
        auto pace_dt = [&](int it, unsigned int dt) {
            if (it >= WINDOW) mbar_wait(BAR(0) + (it - WINDOW) * 8);
            int spin_it = 0;
#pragma unroll 1
            while ((int)(gtimer_lo() - due) < 0 && ++spin_it < SPIN_LIMIT) {}
            due += dt;
        };
                auto pace = [&](int it) { pace_dt(it, it < B_KV ? DT_F : (it < B_W1 ? DT_T : DT_T2)); };
        auto tile128 = [&](const CUtensorMap* m, int first, uint32_t dst, int k0) {
#pragma unroll 1
            for (int k = k0; k < 4; k++) {
                pace(first + k);
                tma2d(dst + k * 8192, m, hh * 128 + (k >> 1) * 64, jj * 128 + (k & 1) * 64, BAR(0) + (first + k) * 8, 8192, pol);
            }
        };
        tile128(&p.wq, B_WQ, sb + OFF_Y, 1);
        asm volatile("bar.sync 5, 320;" ::: "memory");
        TS(57);
        tile128(&p.wuk, B_WUK, sb + OFF_X, 0);
        TS(61);
#pragma unroll 1
        for (int s = 0; s < 16; s++) {
            pace_dt(B_KV + s, mbar_test(BAR(B_QABS)) ? DT_S : DT_F);
            tma2d(sb + OFF_KV + s * 8192, &p.kv, (s & 7) * 64, bb * 4096 + chunk * 128 + (s >> 3) * 64, BAR(B_KV) + s * 8, 8192, pol);
        }
        TS(43);
        mbar_wait(BAR(B_YFREE));
        auto mod_items = [&]() {
#pragma unroll 1
            for (int k = 0; k < 2; k++) {
                pace(B_MOD + k);
                tma2d(sb + OFF_Z + k * 8192, &p.wmod, 1024 + 16 * i, k * 256, BAR(B_MOD) + k * 8, 8192, pol);
            }
        };
        mod_items();
        tile128(&p.wuv, B_WUV, sb + OFF_Y, 0);
        mbar_wait(BAR(B_XFREE));
#pragma unroll 1
        for (int k = 0; k < 4; k++) {
            pace(B_WO + k);
            tma3d(sb + OFF_X + k * 8192, &p.wo, 0, hh * 128 + jj * 32, k * 2, BAR(B_WO) + k * 8, 8192, pol);
        }
        if (i < NFFN) {
            mbar_wait(BAR(B_G4));
            due = gtimer_lo();
            mbar_wait(BAR(B_ZFREE));
#pragma unroll 1
            for (int k = 0; k < 2; k++) {
                pace(B_W1 + k);
                tma2d(sb + OFF_Z + k * 8192, &p.w1, 16 * i, k * 256, BAR(B_W1) + k * 8, 8192, pol);
            }
            mbar_wait(BAR(B_KV0FREE));
#pragma unroll 1
            for (int k = 0; k < 2; k++) {
                pace(B_W2 + k);
                tma3d(sb + OFF_W2 + k * 8192, &p.w2, 0, 16 * i, k * 4, BAR(B_W2) + k * 8, 8192, pol);
            }
        }
        TS(40);
    } else if (warp == 9) {
        unsigned int ep = 0;
        if (lane == 0) {
            ep = ld_epoch(&g_sync[(i % NSYNC) * 32]);
            mbar_init(BAR(B_YFREE), 8);
            mbar_init(BAR(B_XFREE), 4);
            mbar_init(BAR(B_KV0FREE), 8);
            mbar_init(BAR(B_EP), 1);
            mbar_init(BAR(B_PEER0), 8);
            mbar_init(BAR(B_XCH), 1);
            mbar_init(BAR(B_G4), 1);
            mbar_init(BAR(B_XST), 2);
            mbar_expect_tx(BAR(B_XCH), 16384);
            mbar_expect_tx(BAR(B_XST), 128);
            asm volatile("fence.mbarrier_init.release.cluster;" ::: "memory");
        }
        __syncwarp();
        asm volatile("bar.arrive 5, 320;" ::: "memory");
        asm volatile("bar.arrive 4, 320;" ::: "memory");
        if (lane < 9) prefetch_map(&p.kv + lane);
        const uint4 z = make_uint4(0, 0, 0, 0);
        st128(&g_H[i * 32 + lane], z);
#pragma unroll
        for (int k = 0; k < 4; k++) st128(&g_Q[i * 128 + k * 32 + lane], z);
        uint32_t xr = 0;
        if (lane < 16) {
            const int V = i * 4 + (lane >> 2), e = lane & 3;
            const int m = (V >> 4) * 16 + ((V & 15) >> 1) + (e >> 1) * 8, b = (V & 1) * 2 + (e & 1);
            xr = ldnc16(p.x + b * 512 + m);
        }
        TS(35);
        asm volatile("bar.sync 6, 288;" ::: "memory");
        TS(30);
        __syncwarp();
        if (lane == 0) {
            sts32(MISC + 224, ep);
            asm volatile("st.shared.v4.b32 [%0], {%1,%2,%1,%1};" ::"r"(MISC + 240), "r"(0), "r"(1) : "memory");
            fence_async_smem();
            mbar_arrive(BAR(B_EP));
        }
        TS(31);
        mbar_wait(BAR(B_EP));
        ep = lds32(MISC + 224);
        const uint32_t tag = 1u + 2u * (ep & 1u);
        if (lane < 16) stsf(MISC + 32 + lane * 4, __uint_as_float(xr << 16));
        mbar_wait(BAR(B_P3));
        wait_cnt(&g_sync[(4 + (i & 3)) * 32 + 1], (ep + 1u) * 128u);
        __syncwarp();
        tma3d_mc(sb + OFF_X + rank * 16384, &p.qabs, 0, bb * 32, rank * 4, BAR(B_QABS), 32768);
        TS(41);
#pragma unroll 1
        for (int k = 0; k < 4; k++) st128(&g_C[i * 128 + k * 32 + lane], z);
        if (lane < 8) st128(&g_X1[i * 8 + lane], z);
        if (lane < 16) st128(&g_M[i * 16 + lane], z);
#pragma unroll 1
        for (int k = 0; k < 16; k++) { st128(&g_O[i * 512 + k * 32 + lane], z); if (i < NFFN) st128(&g_F[i * 512 + k * 32 + lane], z); spin(100); }
        __syncwarp();
        if (lane == 0) mbar_arrive(BAR(B_CLR2));
        TS(44);
        mbar_wait_n(BAR(B_MOD), 2);
        float d[4] = {0.f, 0.f, 0.f, 0.f};
        gemv_512x16(d, sb + OFF_Z, sb + OFF_S, 0, 16, lane);
        __syncwarp();
        if (lane == 0) mbar_arrive(BAR(B_ZFREE));
        if ((lane & 3) < 2) put4(&g_M[i * 16 + (lane >> 2) * 2 + (lane & 3)], d[0], d[1], d[2], d[3], tag);
        __syncwarp();
        if (lane == 0 && i >= 32 && i < 96) red_cnt(&g_sync[4 * 32 + 2]);
        TS(42);
        {
            const float4 v = get4(&g_M[((lane >> 2) & 1) * 3 * 512 + i * 4 + (lane & 3)], lane < 8, tag);
            if (lane < 8) stsf4(MISC + 96 + lane * 16, v);
        }
        __syncwarp();
        if (lane == 0) {
            if (i < NFFN) {
                wait_cnt(&g_sync[4 * 32 + 2], (ep + 1u) * 64u);
                mbar_wait(BAR(B_KV0FREE));
                asm volatile("fence.proxy.async.global;" ::: "memory");
                mbar_expect_tx(BAR(B_MODV), 16384);
                asm volatile("cp.async.bulk.shared::cluster.global.mbarrier::complete_tx::bytes [%0], [%1], %2, [%3];"
                             ::"r"(sb + OFF_SBCB), "l"(&g_M[512]), "r"(16384), "r"(BAR(B_MODV)) : "memory");
            } else {
                mbar_arrive(BAR(B_MODV));
            }
            TS(45);
        }
    } else {
        const uint32_t ACT = sb + OFF_ACT, ACTB = sb + OFF_ACT + 1152, RED = sb + OFF_RED;
        const int g = lane >> 2, q = lane & 3;
        const int vrr = (lane & 15) >> 1, vb0 = (lane & 1) * 2;
        uint32_t cw[4];
        uint4 xv[2];
        uint32_t xh[4];
        TS0(32);
        {
            const uint4* xp = reinterpret_cast<const uint4*>(p.x + (warp & 3) * 512 + lane * 16);
            xv[0] = ldnc128_if(xp, warp < 4);
            xv[1] = ldnc128_if(xp + 1, warp < 4);
            const __nv_bfloat16* xq = p.x + vb0 * 512 + jj * 128 + warp * 16 + vrr;
            xh[0] = ldnc16(xq); xh[1] = ldnc16(xq + 512); xh[2] = ldnc16(xq + 8); xh[3] = ldnc16(xq + 520);
        }
#pragma unroll
        for (int b = 0; b < 4; b++) cw[b] = ldnc32(p.c + b * 512 + 2 * t);
        if (lane == 0) {
#pragma unroll
            for (int k = 0; k < 5; k++) {
                int idx = 4 + warp * 5 + k;
                if (idx >= B_YFREE) idx = (idx == 39) ? B_ZFREE : (idx == 40 ? B_P3 : (idx == 41 ? B_CLR2 : B_MODV));
                mbar_init(BAR(0) + idx * 8, 1);
            }
            asm volatile("fence.mbarrier_init.release.cluster;" ::: "memory");
        }
        __syncwarp();
        asm volatile("bar.arrive 5, 320;" ::: "memory");
        asm volatile("bar.arrive 6, 288;" ::: "memory");
        TS(48 + warp);
        asm volatile("bar.sync 4, 320;" ::: "memory");
        TS0(29);

#pragma unroll
        for (int b = 0; b < 4; b++) {
            const float c0 = bf_lo(cw[b]), c1 = bf_hi(cw[b]);
            sts32(sb + OFF_S + b * 1040 + t * 4, pack_bf16(__fdividef(c0, 1.f + __expf(-c0)), __fdividef(c1, 1.f + __expf(-c1))));
        }
        if (warp < 4) {
            const uint32_t u[8] = {xv[0].x, xv[0].y, xv[0].z, xv[0].w, xv[1].x, xv[1].y, xv[1].z, xv[1].w};
            float s = 0.f, ss = 0.f;
#pragma unroll
            for (int k = 0; k < 8; k++) s += bf_lo(u[k]) + bf_hi(u[k]);
#pragma unroll
            for (int o = 16; o; o >>= 1) s += __shfl_xor_sync(~0u, s, o);
            const float mean = s * (1.f / 512.f);
#pragma unroll
            for (int k = 0; k < 8; k++) { const float d0 = bf_lo(u[k]) - mean, d1 = bf_hi(u[k]) - mean; ss += d0 * d0 + d1 * d1; }
#pragma unroll
            for (int o = 16; o; o >>= 1) ss += __shfl_xor_sync(~0u, ss, o);
            if (lane == 0) { stsf(MISC + warp * 8, mean); stsf(MISC + warp * 8 + 4, rsqrtf(ss * (1.f / 512.f) + 1e-5f)); }
        }
        bar_main();
        mbar_wait(BAR(B_EP));
        const unsigned int ep = lds32(MISC + 224);
        const uint32_t tag = 1u + 2u * (ep & 1u);
        if (warp < 2) {
            mbar_wait(BAR(B_WA));
            TS0(26);
            float d[4] = {0.f, 0.f, 0.f, 0.f};
            gemv_512x16(d, sb + OFF_Z + warp * 4096 - jj * 4096, sb + OFF_S, jj * 128, 4, lane);
            if (q < 2) put4(&g_H[i * 32 + warp * 16 + g * 2 + q], d[0], d[1], d[2], d[3], tag);
        }
        TS0(1);
        mbar_wait_n(BAR(B_WQ), 4);
        TS0(3);
        {
            const float4 a = get4sum4(&g_H[(4 * (8 * jj + warp)) * 32 + lane], 32, tag);
            const float cx = __shfl_down_sync(~0u, a.x, 16), cy = __shfl_down_sync(~0u, a.y, 16);
            const float cz = __shfl_down_sync(~0u, a.z, 16), cwv = __shfl_down_sync(~0u, a.w, 16);
            if (lane < 16) {
                const float2 s0 = ldsf2(MISC + vb0 * 8), s1 = ldsf2(MISC + vb0 * 8 + 8);
                sts_frag(ACT, 272, warp * 16 + vrr, vb0,
                         (__uint_as_float(xh[0] << 16) - s0.x) * s0.y * (1.f + cx) + a.x,
                         (__uint_as_float(xh[1] << 16) - s1.x) * s1.y * (1.f + cy) + a.y,
                         (__uint_as_float(xh[2] << 16) - s0.x) * s0.y * (1.f + cz) + a.z,
                         (__uint_as_float(xh[3] << 16) - s1.x) * s1.y * (1.f + cwv) + a.w);
            }
        }
        bar_main();
        TS0(2);
        gemv_y_put(&g_Q[i * 128], ACT, tag);
        __syncwarp();
        if (lane == 0) mbar_arrive(BAR(B_YFREE));
        mbar_wait_n(BAR(B_WUK), 4);
        TS0(5);
        if (warp < 4) {
            const float4 a = get4sum4(&g_Q[hh * 4 * 128 + t], 128, tag);
            sts_frag(ACTB, 272, (t >> 4) * 16 + vrr, vb0, a.x, a.y, a.z, a.w);
        }
        bar_main();
        TS0(4);
        {
            float d[4] = {0.f, 0.f, 0.f, 0.f};
            const int blk = lane >> 3, r8 = lane & 7;
            const uint32_t arow = sb + OFF_X + (warp * 16 + (blk & 1) * 8 + r8) * 128;
            const uint32_t brow = ACTB + (r8 & 3) * 272 + blk * 16;
            uint32_t a[8][4], b[4][4];
#pragma unroll
            for (int k = 0; k < 8; k++) ldsm4(a[k], arow + (k >> 2) * 16384 + ((((k & 3) * 2 + (blk >> 1)) ^ r8) << 4));
#pragma unroll
            for (int k = 0; k < 4; k++) ldsm4(b[k], brow + k * 64);
            float e[4] = {0.f, 0.f, 0.f, 0.f};
#pragma unroll
            for (int k = 0; k < 4; k++) {
                mma16816(d, a[2 * k], b[k][0], b[k][1]);
                mma16816(e, a[2 * k + 1], b[k][2], b[k][3]);
            }
            d[0] += e[0]; d[1] += e[1]; d[2] += e[2]; d[3] += e[3];
            const float sc = 0.08838834764831845f * 1.4426950408889634f;
            if (q < 2) sts_frag(RED, 256, warp * 16 + g, 2 * q, d[0] * sc, d[1] * sc, d[2] * sc, d[3] * sc);
            fence_async_smem();
            bar_main();
            if (t == 0) {
#pragma unroll 1
                for (int b = 0; b < 4; b++) bulk_s2g(&g_qabs[(b * 32 + hh) * 512 + jj * 128], RED + b * 256, 256);
                asm volatile("cp.async.bulk.commit_group;" ::: "memory");
                asm volatile("cp.async.bulk.wait_group 0;" ::: "memory");
#pragma unroll
                for (int r = 0; r < 4; r++) red_cnt(&g_sync[(4 + r) * 32 + 1]);
                mbar_arrive(BAR(B_P3));
            }
            TS0(6);
        }
        const int wg = warp >> 2, wq = warp & 3;
        {
            const uint32_t MX = RED;
            const uint32_t LRED = RED + 512;
            const uint32_t OST = ACTB + 128, PST = ACTB;
            const uint32_t ALPHA = RED + 1536, MRUN = RED + 1664;
            float o[4][16];
            float lsum[8];
#pragma unroll
            for (int k = 0; k < 8; k++) lsum[k] = 0.f;
            if (t < 32) stsf(MRUN + t * 4, -INFINITY);
            mbar_wait(BAR(B_QABS));
            TS0(7);
            float s[16];
            auto qk = [&](int c0, int c1) {
                uint32_t da = desc_lo(SB0 + OFF_KV) + wg * (65536 >> 4) + c0 * (8192 >> 4), db = desc_lo(SB0 + OFF_X) + c0 * (4096 >> 4);
#pragma unroll 1
                for (int cb = c0; cb < c1; cb++) {
                    mbar_wait(BAR(B_KV) + (wg * 8 + cb) * 8);
                    wg_fence();
#pragma unroll
                    for (int k = 0; k < 4; k++) wgmma_n32<0>(s, da + k * 2, db + k * 2, (cb | k) != 0);
                    wg_commit();
                    da += 8192 >> 4;
                    db += 4096 >> 4;
                }
            };
            if (wg == 1) qk(0, QK_EARLY);
#pragma unroll 1
            for (int tile = 0; tile < 2; tile++) {
                if (wg == tile) {
                    qk(tile == 0 ? 0 : QK_EARLY, 8);
                    wg_wait0();
                    reg_fence(s);
                    if (tile == 1) {
                        __syncwarp();
                        if (lane == 0) {
                            mbar_arrive(BAR(B_XFREE));
                            mbar_arrive(BAR(B_KV0FREE));
                            asm volatile("mbarrier.arrive.relaxed.cluster.shared::cluster.b64 _, [%0];" ::"r"(mapa(BAR(B_PEER0), rank ^ 1)) : "memory");
                        }
                    }
                    if (wq == 0) TS(8 + tile * 2);
                    float m[8];
#pragma unroll
                    for (int jb = 0; jb < 4; jb++) {
                        m[2 * jb] = fmaxf(s[4 * jb], s[4 * jb + 2]);
                        m[2 * jb + 1] = fmaxf(s[4 * jb + 1], s[4 * jb + 3]);
                    }
#pragma unroll
                    for (int of = 4; of <= 16; of <<= 1) {
#pragma unroll
                        for (int k = 0; k < 8; k++) m[k] = fmaxf(m[k], __shfl_xor_sync(~0u, m[k], of));
                    }
                    if (g == 0) {
#pragma unroll
                        for (int jb = 0; jb < 4; jb++)
                            asm volatile("st.shared.v2.f32 [%0], {%1,%2};" ::"r"(MX + (wq * 32 + 8 * jb + 2 * q) * 4), "f"(m[2 * jb]), "f"(m[2 * jb + 1]) : "memory");
                    }
                    if (tile == 0) asm volatile("bar.sync 2, 128;" ::: "memory"); else asm volatile("bar.sync 3, 128;" ::: "memory");
                    const float mold = ldsf(MRUN + tile * 128 + lane * 4);
                    const float mnew = fmaxf(fmaxf(fmaxf(ldsf(MX + lane * 4), ldsf(MX + 128 + lane * 4)), fmaxf(ldsf(MX + 256 + lane * 4), ldsf(MX + 384 + lane * 4))), mold);
                    uint32_t lo[4], hi[4];
#pragma unroll
                    for (int jb = 0; jb < 4; jb++) {
                        const float m0 = __shfl_sync(~0u, mnew, 8 * jb + 2 * q), m1 = __shfl_sync(~0u, mnew, 8 * jb + 2 * q + 1);
                        lo[jb] = pack_bf16(ex2(s[4 * jb] - m0), ex2(s[4 * jb + 1] - m1));
                        hi[jb] = pack_bf16(ex2(s[4 * jb + 2] - m0), ex2(s[4 * jb + 3] - m1));
                        lsum[2 * jb] = bf_lo(lo[jb]) + bf_lo(hi[jb]);
                        lsum[2 * jb + 1] = bf_hi(lo[jb]) + bf_hi(hi[jb]);
                    }
                    const uint32_t prow = sb + OFF_P + tile * 4096 + ((lane + 16 * rank) & 31) * 128;
                    stsm4t(prow + (((2 * wq) ^ (lane & 7)) << 4), lo[0], lo[1], lo[2], lo[3]);
                    stsm4t(prow + (((2 * wq + 1) ^ (lane & 7)) << 4), hi[0], hi[1], hi[2], hi[3]);
                    fence_async_smem();
                    if (wq == 0) { stsf(ALPHA + lane * 4, ex2(mold - mnew)); stsf(MRUN + (tile + 1) * 128 + lane * 4, mnew); }
                }
                bar_main();
                TS0(27 + tile);
                if (tile == 1) {
                    wg_wait0();
#pragma unroll
                    for (int mt = 0; mt < 4; mt++) reg_fence(o[mt]);
#pragma unroll
                    for (int jb = 0; jb < 4; jb++) {
                        const float2 a = ldsf2(ALPHA + ((8 * jb + 2 * q + 16 * rank) & 31) * 4);
#pragma unroll
                        for (int mt = 0; mt < 4; mt++) { o[mt][4 * jb] *= a.x; o[mt][4 * jb + 1] *= a.y; o[mt][4 * jb + 2] *= a.x; o[mt][4 * jb + 3] *= a.y; }
                    }
                }
                {
                    const uint32_t da = desc_lo(SB0 + OFF_KV) + tile * (65536 >> 4) + wg * (32768 >> 4), db = desc_lo(SB0 + OFF_P) + tile * (4096 >> 4);
                    wg_fence();
#pragma unroll
                    for (int mt = 0; mt < 4; mt++) {
#pragma unroll
                        for (int k = 0; k < 4; k++)
                            wgmma_n32<1>(o[mt], da + mt * (8192 >> 4) + k * (2048 >> 4), db + k * 2, tile | k);
                        wg_commit();
                    }
                }
                if (wg == tile) {
#pragma unroll
                    for (int of = 4; of <= 16; of <<= 1) {
#pragma unroll
                        for (int k = 0; k < 8; k++) lsum[k] += __shfl_xor_sync(~0u, lsum[k], of);
                    }
                    if (g == 0) {
#pragma unroll
                        for (int jb = 0; jb < 4; jb++)
                            asm volatile("st.shared.v2.f32 [%0], {%1,%2};" ::"r"(LRED + (warp * 32 + 8 * jb + 2 * q) * 4), "f"(lsum[2 * jb]), "f"(lsum[2 * jb + 1]) : "memory");
                    }
                    if (tile == 1) {
                        asm volatile("bar.sync 3, 128;" ::: "memory");
                        if (wq == 0) {
                            float l0 = 0.f, l1 = 0.f;
#pragma unroll
                            for (int w = 0; w < 4; w++) { l0 += ldsf(LRED + (w * 32 + lane) * 4); l1 += ldsf(LRED + ((w + 4) * 32 + lane) * 4); }
                            const float l = l0 * ldsf(ALPHA + lane * 4) + l1;
                            const float mf = ldsf(MRUN + 256 + lane * 4);
                            if ((lane >> 4) == (int)rank) {
                                asm volatile("st.shared.v2.f32 [%0], {%1,%2};" ::"r"(OST + (lane & 15) * 8), "f"(mf), "f"(l) : "memory");
                            } else {
                                mbar_wait(BAR(B_PEER0));
                                st_async2(mapa(PST + (lane & 15) * 8, rank ^ 1), mf, l, mapa(BAR(B_XST), rank ^ 1));
                            }
                            __syncwarp();
                            if (lane == 0) mbar_arrive(BAR(B_XST));
                        }
                    }
                }
                if (tile == 0 && wg == 0) {
                    wg_wait0();
                    __syncwarp();
                    if (lane == 0) {
                        mbar_arrive(BAR(B_KV0FREE));
                        asm volatile("mbarrier.arrive.relaxed.cluster.shared::cluster.b64 _, [%0];" ::"r"(mapa(BAR(B_PEER0), rank ^ 1)) : "memory");
                    }
                    TS0(9);
                }
            }
            mbar_wait(BAR(B_PEER0));
            {
                const uint32_t rx = mapa(sb + OFF_XCH + t * 16, rank ^ 1), rb = mapa(BAR(B_XCH), rank ^ 1);
                asm volatile("wgmma.wait_group.sync.aligned 3;" ::: "memory");
                reg_fence(o[0]);
                st_async4(rx, pack_bf16(o[0][8], o[0][9]), pack_bf16(o[0][10], o[0][11]), pack_bf16(o[0][12], o[0][13]), pack_bf16(o[0][14], o[0][15]), rb);
                asm volatile("wgmma.wait_group.sync.aligned 2;" ::: "memory");
                reg_fence(o[1]);
                st_async4(rx + 4096, pack_bf16(o[1][8], o[1][9]), pack_bf16(o[1][10], o[1][11]), pack_bf16(o[1][12], o[1][13]), pack_bf16(o[1][14], o[1][15]), rb);
                asm volatile("wgmma.wait_group.sync.aligned 1;" ::: "memory");
                reg_fence(o[2]);
                st_async4(rx + 8192, pack_bf16(o[2][8], o[2][9]), pack_bf16(o[2][10], o[2][11]), pack_bf16(o[2][12], o[2][13]), pack_bf16(o[2][14], o[2][15]), rb);
                wg_wait0();
                reg_fence(o[3]);
                st_async4(rx + 12288, pack_bf16(o[3][8], o[3][9]), pack_bf16(o[3][10], o[3][11]), pack_bf16(o[3][12], o[3][13]), pack_bf16(o[3][14], o[3][15]), rb);
            }
            TS0(11);
            mbar_wait(BAR(B_XST));
            float ca[4], cb[4];
#pragma unroll
            for (int k = 0; k < 4; k++) {
                const int n = 8 * (k >> 1) + 2 * q + (k & 1);
                const float2 so = ldsf2(OST + n * 8), sp = ldsf2(PST + n * 8);
                const float mx = fmaxf(so.x, sp.x);
                ca[k] = ex2(so.x - mx);
                cb[k] = ex2(sp.x - mx);
            }
#pragma unroll
            for (int mt = 0; mt < 4; mt++) {
                o[mt][0] *= ca[0]; o[mt][1] *= ca[1]; o[mt][2] *= ca[0]; o[mt][3] *= ca[1];
                o[mt][4] *= ca[2]; o[mt][5] *= ca[3]; o[mt][6] *= ca[2]; o[mt][7] *= ca[3];
            }
            if (warp == 0) {
                const float2 so = ldsf2(OST + (lane & 15) * 8), sp = ldsf2(PST + (lane & 15) * 8);
                const float mx = fmaxf(so.x, sp.x);
                const float l = so.y * ex2(so.x - mx) + sp.y * ex2(sp.x - mx);
                const float ln = __shfl_down_sync(~0u, l, 1), mn = __shfl_down_sync(~0u, mx, 1);
                if (lane < 16 && (lane & 1) == 0) put4(&g_stat[((rank * 4 + (lane >> 2)) * 64 + (i >> 1)) * 2 + ((lane >> 1) & 1)], mx, l, mn, ln, tag);
            }
            const uint32_t keep = (g == 0) ? 0xFFFEFFFEu : 0xFFFFFFFFu;
            const uint32_t tg = (g == 0) ? ((ep & 1u) ? 0u : 0x00010001u) : 0u;
            const int hl = lane & 15, mi2 = lane >> 4;
            mbar_wait(BAR(B_XCH));
            TS0(46);
#pragma unroll
            for (int mt = 0; mt < 4; mt++) {
                const uint4 r = lds128(sb + OFF_XCH + mt * 4096 + t * 16);
                const uint32_t lo0 = (pack_bf16(o[mt][0] + cb[0] * bf_lo(r.x), o[mt][1] + cb[1] * bf_hi(r.x)) & keep) | tg;
                const uint32_t hi0 = (pack_bf16(o[mt][2] + cb[0] * bf_lo(r.y), o[mt][3] + cb[1] * bf_hi(r.y)) & keep) | tg;
                const uint32_t lo1 = (pack_bf16(o[mt][4] + cb[2] * bf_lo(r.z), o[mt][5] + cb[3] * bf_hi(r.z)) & keep) | tg;
                const uint32_t hi1 = (pack_bf16(o[mt][6] + cb[2] * bf_lo(r.w), o[mt][7] + cb[3] * bf_hi(r.w)) & keep) | tg;
                const uint32_t row = sb + OFF_STG + (wg * 2 + (mt >> 1)) * 4096 + hl * 256;
                const int ch = (mt & 1) * 8 + wq * 2 + mi2;
                stsm4t(row + ((ch ^ (hl & 7)) << 4), lo0, lo1, hi0, hi1);
            }
            fence_async_smem();
            if (wg == 0) asm volatile("bar.sync 2, 128;" ::: "memory"); else asm volatile("bar.sync 3, 128;" ::: "memory");
            if (warp == 4) TS(47);
            if (wq == 0 && lane == 0) {
                bulk_s2g(&g_part[i * 1024 + wg * 512], sb + OFF_STG + wg * 8192, 8192);
                asm volatile("cp.reduce.async.bulk.global.shared::cta.bulk_group.add.u32 [%0], [%1], 16;" ::"l"(&g_sync[bb * 32]), "r"(MISC + 240) : "memory");
                asm volatile("cp.async.bulk.commit_group;" ::: "memory");
            }
            TS0(12);
        }
        mbar_wait(BAR(B_CLR2));
        TS0(15);
        const uint32_t SCR = sb + OFF_SCR;
        {
            const int b = warp >> 1;
            const uint32_t ptag = (ep & 1u) ? 0u : 1u;
            const int pi = lane >> 3, v = (warp & 1) * 8 + (lane & 7);
            const uint4* sp = &g_stat[((hh >> 2) * 64 + b * 16 + (lane & 15)) * 2 + ((hh >> 1) & 1)];
            const uint4* src = &g_part[(2 * (b * 16 + pi) + (hh >> 4)) * 1024 + (jj * 16 + (hh & 15)) * 16 + v];
            float acc[8];
            int it = 0;
            bool ok;
            TS0(62);
            if (warp != 0) mbar_wait_n(BAR(B_WUV), 4);
            if (warp == 0) {
                const unsigned int target = (ep + 1u) * 64u;
                spin(GATEDELAY);
#pragma unroll 1
                while (!__all_sync(~0u, (int)(ld_cnt(&g_sync[(lane & 3) * 32 + 1]) - target) >= 0) && ++it < SPIN_LIMIT) { spin(POLLGAP); }
                it = 0;
                if (lane == 0) mbar_arrive(BAR(B_G4));
            }
            bar_main();
            TS0(13);
#pragma unroll 1
            do {
                const uint4 su = ld128(sp);
                uint4 r[4];
#pragma unroll
                for (int k = 0; k < 4; k++) r[k] = ld128(src + (size_t)k * 8 * 1024);
                ok = (su.x & 3u) == tag;
                const float mi = (hh & 1) ? __uint_as_float(su.z) : __uint_as_float(su.x & ~3u), li = (hh & 1) ? __uint_as_float(su.w) : __uint_as_float(su.y);
                float mx = mi;
#pragma unroll
                for (int of = 8; of; of >>= 1) mx = fmaxf(mx, __shfl_xor_sync(~0u, mx, of));
                float wi = ex2(mi - mx);
                float L = wi * li;
#pragma unroll
                for (int of = 8; of; of >>= 1) L += __shfl_xor_sync(~0u, L, of);
                wi = __fdividef(wi, L);
#pragma unroll
                for (int k = 0; k < 8; k++) acc[k] = 0.f;
#pragma unroll
                for (int k = 0; k < 4; k++) {
                    const float w = __shfl_sync(~0u, wi, 4 * k + pi);
                    ok = ok & ((r[k].x & 1u) == ptag);
                    acc[0] += w * bf_lo(r[k].x); acc[1] += w * bf_hi(r[k].x);
                    acc[2] += w * bf_lo(r[k].y); acc[3] += w * bf_hi(r[k].y);
                    acc[4] += w * bf_lo(r[k].z); acc[5] += w * bf_hi(r[k].z);
                    acc[6] += w * bf_lo(r[k].w); acc[7] += w * bf_hi(r[k].w);
                }
            } while (!__all_sync(~0u, ok) && ++it < SPIN_LIMIT);
            {
                const bool u4 = lane & 16, u3 = lane & 8;
                float h4[4], h2[2];
#pragma unroll
                for (int k = 0; k < 4; k++) h4[k] = (u4 ? acc[k + 4] : acc[k]) + __shfl_xor_sync(~0u, u4 ? acc[k] : acc[k + 4], 16);
#pragma unroll
                for (int k = 0; k < 2; k++) h2[k] = (u3 ? h4[k + 2] : h4[k]) + __shfl_xor_sync(~0u, u3 ? h4[k] : h4[k + 2], 8);
                const int ch = v ^ (hh & 7);
                sts32(ACT + b * 272 + (ch * 8 + (u4 ? 4 : 0) + (u3 ? 2 : 0)) * 2, pack_bf16(h2[0], h2[1]));
            }
            bar_main();
            TS0(14);
        }
        gemv_y_put(&g_C[i * 128], ACT, tag);
        TS0(17);
        if (warp != 0) mbar_wait_n(BAR(B_WO), 4);
        if (warp == 0) {
            spin(G5DELAY);
            const float4 a = get4sum4(&g_C[hh * 4 * 128 + jj * 32 + lane], 128, tag);
            sts_frag(ACTB, 80, (t >> 4) * 16 + vrr, vb0, a.x, a.y, a.z, a.w);
        }
        bar_main();
        TS0(16);
        {
            const int blk = lane >> 3, r8 = lane & 7;
            uint32_t b[4];
            ldsm4(b, ACTB + (r8 & 3) * 80 + blk * 16);
            const uint32_t wb = sb + OFF_X + warp * 4096 + ((blk >> 1) * 8 + r8) * 128;
#pragma unroll
            for (int mt = 0; mt < 4; mt++) {
                float d[4] = {0.f, 0.f, 0.f, 0.f};
                uint32_t a0[4], a1[4];
                const uint32_t co = ((2 * mt + (blk & 1)) ^ r8) << 4;
                ldsm4t(a0, wb + co);
                ldsm4t(a1, wb + 16 * 128 + co);
                mma16816(d, a0, b[0], b[1]);
                mma16816(d, a1, b[2], b[3]);
                if (q < 2) put4(&g_O[i * 512 + (warp * 4 + mt) * 16 + g * 2 + q], d[0], d[1], d[2], d[3], tag);
            }
            TS0(18);
        }
        const int V = i * 4 + (t & 3);
        const int vm = (V >> 4) * 16 + ((V & 15) >> 1), vb = (V & 1) * 2;
        float4 x1 = make_float4(0.f, 0.f, 0.f, 0.f);
        {
            mbar_wait(BAR(B_MODV));
            const float4 r = reduce16(g_O, 128, tag, G6ADELAY);
            if (t < 4) {
                const float4 x0 = ldsf4(MISC + 32 + t * 16), ga = ldsf4(MISC + 96 + t * 16);
                x1 = make_float4(x0.x + ga.x * r.x, x0.y + ga.y * r.y, x0.z + ga.z * r.z, x0.w + ga.w * r.w);
                put4(&g_X1[i * 8 + t], x1.x, x1.y, x1.z, x1.w, tag);
            }
            TS0(19);
        }
        if (i < NFFN) {
            float4 mv[4];
#pragma unroll
            for (int k = 0; k < 4; k++) {
                uint4 u = lds128(sb + OFF_SBCB + (t + 256 * k) * 16);
                int it = 0;
                while ((u.x & 3u) != tag && ++it < SPIN_LIMIT) u = ld128(&g_M[512 + t + 256 * k]);
                mv[k] = as_f4(u);
            }
            mbar_wait_n(BAR(B_W1), 4);
            TS0(21);
            uint4 ua, ub;
            {
                int it = 0;
                do { ua = ld128(&g_X1[(t >> 2) * 8 + (t & 3)]); ub = ld128(&g_X1[(t >> 2) * 8 + (t & 3) + 512]); } while (!__all_sync(~0u, (ua.x & 3u) == tag && (ub.x & 3u) == tag) && ++it < SPIN_LIMIT);
            }
            const float4 a = as_f4(ua), b = as_f4(ub);
            float s0 = (a.x + a.z) + (b.x + b.z), s1 = (a.y + a.w) + (b.y + b.w);
            float q0 = (a.x * a.x + a.z * a.z) + (b.x * b.x + b.z * b.z), q1 = (a.y * a.y + a.w * a.w) + (b.y * b.y + b.w * b.w);
#pragma unroll
            for (int of = 2; of <= 16; of <<= 1) {
                s0 += __shfl_xor_sync(~0u, s0, of); s1 += __shfl_xor_sync(~0u, s1, of);
                q0 += __shfl_xor_sync(~0u, q0, of); q1 += __shfl_xor_sync(~0u, q1, of);
            }
            const uint32_t ST = SCR + 1024, ACT2 = SCR + 4096;
            if (lane < 2) stsf4(ST + (warp * 2 + lane) * 16, make_float4(s0, q0, s1, q1));
            bar_main();
            TS0(20);
            float4 tot = make_float4(0.f, 0.f, 0.f, 0.f);
#pragma unroll
            for (int w = 0; w < 8; w++) add4(tot, ldsf4(ST + (w * 2 + (t & 1)) * 16));
            const float mean0 = tot.x * (1.f / 512.f), mean1 = tot.z * (1.f / 512.f);
            const float r0 = rsqrtf(fmaxf(tot.y * (1.f / 512.f) - mean0 * mean0, 0.f) + 1e-5f);
            const float r1 = rsqrtf(fmaxf(tot.w * (1.f / 512.f) - mean1 * mean1, 0.f) + 1e-5f);
            const int m0 = (t >> 4) * 16 + vrr;
            sts_frag(ACT2, 1040, m0, vb0, (a.x - mean0) * r0 * (1.f + mv[2].x) + mv[0].x, (a.y - mean1) * r1 * (1.f + mv[2].y) + mv[0].y,
                     (a.z - mean0) * r0 * (1.f + mv[2].z) + mv[0].z, (a.w - mean1) * r1 * (1.f + mv[2].w) + mv[0].w);
            sts_frag(ACT2, 1040, m0 + 256, vb0, (b.x - mean0) * r0 * (1.f + mv[3].x) + mv[1].x, (b.y - mean1) * r1 * (1.f + mv[3].y) + mv[1].y,
                     (b.z - mean0) * r0 * (1.f + mv[3].z) + mv[1].z, (b.w - mean1) * r1 * (1.f + mv[3].w) + mv[1].w);
            bar_main();
            float d[4] = {0.f, 0.f, 0.f, 0.f};
            gemv_512x16(d, sb + OFF_Z, ACT2, warp * 64, 2, lane);
            const uint32_t HR = SCR + 2048;
            if (q < 2) {
                const uint32_t a0 = HR + (warp * 64 + (2 * q) * 16 + g) * 4;
                stsf(a0, d[0]); stsf(a0 + 64, d[1]); stsf(a0 + 32, d[2]); stsf(a0 + 96, d[3]);
            }
            bar_main();
            float2 h0 = make_float2(0.f, 0.f), h1 = h0;
#pragma unroll
            for (int w = 0; w < 8; w++) {
                const float2 u = ldsf2(HR + (w * 64 + (g & 3) * 16 + 2 * q) * 4), v = ldsf2(HR + (w * 64 + (g & 3) * 16 + 2 * q + 8) * 4);
                h0.x += u.x; h0.y += u.y; h1.x += v.x; h1.y += v.y;
            }
            const uint32_t b0r = pack_bf16(fmaxf(h0.x, 0.f), fmaxf(h0.y, 0.f)), b1r = pack_bf16(fmaxf(h1.x, 0.f), fmaxf(h1.y, 0.f));
            TS0(22);
            const int blk = lane >> 3, r8 = lane & 7;
            const uint32_t wb = sb + OFF_W2 + warp * 2048 + ((blk >> 1) * 8 + r8) * 128;
#pragma unroll
            for (int mt = 0; mt < 4; mt++) {
                float e[4] = {0.f, 0.f, 0.f, 0.f};
                uint32_t a0[4];
                ldsm4t(a0, wb + (((2 * mt + (blk & 1)) ^ r8) << 4));
                mma16816(e, a0, b0r, b1r);
                if (q < 2) put4(&g_F[i * 512 + (warp * 4 + mt) * 16 + g * 2 + q], e[0], e[1], e[2], e[3], tag);
            }
            TS0(23);
        }
        {
            const float4 r = reduce16(g_F, NFFN, tag, i < NFFN ? HOPDELAY : FFNDELAY);
            if (t < 4) {
                const float4 gb = ldsf4(MISC + 96 + 64 + t * 16);
                p.out[vb * 512 + vm] = __float2bfloat16_rn(x1.x + gb.x * r.x);
                p.out[(vb + 1) * 512 + vm] = __float2bfloat16_rn(x1.y + gb.y * r.y);
                p.out[vb * 512 + vm + 8] = __float2bfloat16_rn(x1.z + gb.z * r.z);
                p.out[(vb + 1) * 512 + vm + 8] = __float2bfloat16_rn(x1.w + gb.w * r.w);
            }
            if ((t & 127) == 0) asm volatile("cp.async.bulk.wait_group 0;" ::: "memory");
            if (i == 0 && t < NSYNC) g_sync[t * 32] = ep + 1u;
            TS0(24);
        }
    }
}

typedef CUresult (*EncodeFn)(CUtensorMap*, CUtensorMapDataType, cuuint32_t, void*, const cuuint64_t*, const cuuint64_t*, const cuuint32_t*,
                             const cuuint32_t*, CUtensorMapInterleave, CUtensorMapSwizzle, CUtensorMapL2promotion, CUtensorMapFloatOOBfill);

void make_map(EncodeFn enc, CUtensorMap* m, const void* base, int rank, const cuuint64_t* dims, const cuuint64_t* strides, const cuuint32_t* box,
              CUtensorMapSwizzle sw) {
    cuuint32_t es[3] = {1, 1, 1};
    CUresult r = enc(m, CU_TENSOR_MAP_DATA_TYPE_BFLOAT16, rank, const_cast<void*>(base), dims, strides, box, es, CU_TENSOR_MAP_INTERLEAVE_NONE, sw,
                     CU_TENSOR_MAP_L2_PROMOTION_NONE, CU_TENSOR_MAP_FLOAT_OOB_FILL_NONE);
    if (r != CUDA_SUCCESS) fprintf(stderr, "cuTensorMapEncodeTiled failed: %d\n", (int)r);
}
void map2d(EncodeFn enc, CUtensorMap* m, const void* base, uint64_t rows, uint64_t cols, uint32_t boxr, uint32_t boxc, CUtensorMapSwizzle sw) {
    cuuint64_t dims[2] = {cols, rows};
    cuuint64_t strides[1] = {cols * 2};
    cuuint32_t box[2] = {boxc, boxr};
    make_map(enc, m, base, 2, dims, strides, box, sw);
}
void map3d(EncodeFn enc, CUtensorMap* m, const void* base, uint64_t rows, uint32_t boxr, uint32_t boxb) {
    cuuint64_t dims[3] = {64, rows, 8};
    cuuint64_t strides[2] = {1024, 128};
    cuuint32_t box[3] = {64, boxr, boxb};
    make_map(enc, m, base, 3, dims, strides, box, CU_TENSOR_MAP_SWIZZLE_128B);
}

}

extern "C" void kernel_launch(void* const* d_in, const int* in_sizes, int n_in, void* d_out, int out_size) {
    (void)in_sizes; (void)n_in; (void)out_size;
    static EncodeFn enc = nullptr;
    static void* qabs_ptr = nullptr;
    if (!enc) {
        void* fn = nullptr;
        cudaDriverEntryPointQueryResult st;
        cudaGetDriverEntryPoint("cuTensorMapEncodeTiled", &fn, cudaEnableDefault, &st);
        enc = (EncodeFn)fn;
        cudaFuncSetAttribute(fused_kernel, cudaFuncAttributeMaxDynamicSharedMemorySize, SMEM_BYTES);
        cudaGetSymbolAddress(&qabs_ptr, g_qabs);
    }
    Params p;
    map2d(enc, &p.kv, d_in[1], 16384, 512, 64, 64, CU_TENSOR_MAP_SWIZZLE_128B);
    map2d(enc, &p.wq, d_in[2], 512, 4096, 64, 64, CU_TENSOR_MAP_SWIZZLE_128B);
    map2d(enc, &p.wuk, d_in[3], 512, 4096, 64, 64, CU_TENSOR_MAP_SWIZZLE_128B);
    map2d(enc, &p.wuv, d_in[4], 512, 4096, 64, 64, CU_TENSOR_MAP_SWIZZLE_128B);
    map3d(enc, &p.wo, d_in[5], 4096, 32, 2);
    map2d(enc, &p.w1, d_in[7], 512, 1376, 256, 16, CU_TENSOR_MAP_SWIZZLE_32B);
    map3d(enc, &p.w2, d_in[8], 1376, 16, 4);
    map2d(enc, &p.wmod, d_in[10], 512, 3072, 256, 16, CU_TENSOR_MAP_SWIZZLE_32B);
    map3d(enc, &p.qabs, qabs_ptr, 128, 32, 4);
    map2d(enc, &p.wmoda, d_in[10], 512, 3072, 128, 16, CU_TENSOR_MAP_SWIZZLE_32B);
    p.x = (const __nv_bfloat16*)d_in[0];
    p.c = (const __nv_bfloat16*)d_in[9];
    p.wmodp = (const __nv_bfloat16*)d_in[10];
    p.out = (__nv_bfloat16*)d_out;
    fused_kernel<<<NCTA, NTHREADS, SMEM_BYTES, cudaStreamPerThread>>>(p);
}
```

```cpp
#include <cuda_runtime.h>
#include <cuda_bf16.h>
#include <cuda.h>
#include <stdint.h>
#include <stdio.h>

namespace {

constexpr int NCTA = 128;
constexpr int NTHREADS = 320;
constexpr int NFFN = 86;
#define WINDOW 5
#define WINDOW_S WINDOW
#define WINDOW_T WINDOW
#define DT_F 345
#define DT_0 550
#define DT_S 330
#define DT_T 320
#define DT_T2 200
#define QK_EARLY 4
#define G5DELAY 150
#define G6ADELAY 300
#define FFNDELAY 2600
#define GATE_NS 3600
#define POLLGAP 0
#define HOPDELAY 300

constexpr uint32_t OFF_KV = 0;
constexpr uint32_t OFF_X = 131072;
constexpr uint32_t OFF_Y = 163840;
constexpr uint32_t OFF_Z = 196608;
constexpr uint32_t OFF_P = 212992;
constexpr uint32_t OFF_S = 221184;
constexpr uint32_t OFF_ACT = 225344;
constexpr uint32_t OFF_RED = 227648;
constexpr uint32_t OFF_BAR = 229696;
constexpr uint32_t OFF_MISC = 230208;
constexpr uint32_t SMEM_BYTES = 230720;
constexpr uint32_t OFF_STG = OFF_KV;
constexpr uint32_t OFF_XCH = OFF_KV + 16384;
constexpr uint32_t OFF_W2 = OFF_KV + 32768;
constexpr uint32_t OFF_SBCB = OFF_KV + 49152;
constexpr uint32_t OFF_SCR = OFF_KV + 65536;

enum {
    B_WQ = 0,
    B_WUK = 4,
    B_KV = 8,
    B_MOD = 24,
    B_WUV = 26,
    B_WO = 30,
    B_W1 = 34,
    B_W2 = 36,
    B_QABS = 38,
    B_YFREE = 39,
    B_XFREE = 40,
    B_ZFREE = 41,
    B_KV0FREE = 42,
    B_P3 = 43,
    B_CLR2 = 44,
    B_MODV = 45,
    B_WA = 46,
    B_EP = 47,
    B_PEER0 = 48,
    B_XCH = 49,
    B_G4 = 50,
    B_XST = 51,
    B_COUNT = 52
};

struct alignas(64) Params {
    CUtensorMap kv, wq, wuk, wuv, wo, w1, w2, wmod, qabs, wmoda;
    const __nv_bfloat16* x;
    const __nv_bfloat16* c;
    const __nv_bfloat16* wmodp;
    __nv_bfloat16* out;
};

__device__ __align__(128) uint4 g_H[128 * 32];
__device__ __align__(128) uint4 g_Q[128 * 128];
__device__ __align__(128) __nv_bfloat16 g_qabs[4 * 32 * 512];
__device__ __align__(128) uint4 g_part[128 * 4 * 16 * 16];
__device__ __align__(128) uint4 g_stat[8 * 64 * 2];
__device__ __align__(128) uint4 g_C[128 * 128];
__device__ __align__(128) uint2 g_O[128 * 512];
__device__ __align__(128) uint2 g_X1[128 * 16];
__device__ __align__(128) uint2 g_F[NFFN * 512];
__device__ __align__(128) uint4 g_M[4 * 512];
constexpr int NSYNC = 8;
__device__ __align__(128) unsigned int g_sync[NSYNC * 32];

__device__ __forceinline__ uint32_t smem_u32(const void* p) { return (uint32_t)__cvta_generic_to_shared(p); }
__device__ __forceinline__ void mbar_init(uint32_t bar, int cnt) { asm volatile("mbarrier.init.shared::cta.b64 [%0], %1;" ::"r"(bar), "r"(cnt) : "memory"); }
__device__ __forceinline__ void mbar_expect_tx(uint32_t bar, uint32_t bytes) { asm volatile("mbarrier.arrive.expect_tx.shared::cta.b64 _, [%0], %1;" ::"r"(bar), "r"(bytes) : "memory"); }
__device__ __forceinline__ void mbar_arrive(uint32_t bar) { asm volatile("mbarrier.arrive.shared::cta.b64 _, [%0];" ::"r"(bar) : "memory"); }
constexpr int SPIN_LIMIT = 1 << 20;
__device__ __forceinline__ void mbar_wait(uint32_t bar) {
    asm volatile("{\n.reg .pred p;\n.reg .u32 n;\nmov.u32 n, 0;\n"
                 "LW:\nmbarrier.try_wait.parity.shared::cta.b64 p, [%0], 0;\n@p bra LD;\n"
                 "add.u32 n, n, 1;\nsetp.lt.u32 p, n, 4194304;\n@p bra LW;\nLD:\n}" ::"r"(bar) : "memory");
}
__device__ __forceinline__ bool mbar_test(uint32_t bar) {
    uint32_t ok;
    asm volatile("{\n.reg .pred p;\nmbarrier.test_wait.parity.shared::cta.b64 p, [%1], 0;\nselp.u32 %0, 1, 0, p;\n}" : "=r"(ok) : "r"(bar) : "memory");
    return ok;
}
__device__ __forceinline__ void mbar_wait_n(uint32_t bar, int n) {
#pragma unroll 1
    for (int k = 0; k < n; k++) mbar_wait(bar + k * 8);
}
__device__ __forceinline__ void bar_main() { asm volatile("bar.sync 1, 256;" ::: "memory"); }
__device__ __forceinline__ void fence_async_smem() { asm volatile("fence.proxy.async.shared::cta;" ::: "memory"); }

__device__ __forceinline__ uint4 ld128(const uint4* p) {
    uint4 v;
    asm volatile("{\n.reg .b128 t;\n.reg .b64 lo, hi;\nld.relaxed.gpu.global.b128 t, [%4];\nmov.b128 {lo, hi}, t;\nmov.b64 {%0,%1}, lo;\nmov.b64 {%2,%3}, hi;\n}"
                 : "=r"(v.x), "=r"(v.y), "=r"(v.z), "=r"(v.w) : "l"(p) : "memory");
    return v;
}
__device__ __forceinline__ void st128(uint4* p, uint4 v) {
    asm volatile("{\n.reg .b128 t;\n.reg .b64 lo, hi;\nmov.b64 lo, {%1,%2};\nmov.b64 hi, {%3,%4};\nmov.b128 t, {lo, hi};\nst.relaxed.gpu.global.b128 [%0], t;\n}"
                 ::"l"(p), "r"(v.x), "r"(v.y), "r"(v.z), "r"(v.w) : "memory");
}
__device__ __forceinline__ uint4 ldnc128_if(const void* p, bool c) {
    uint4 v;
    asm volatile("{\n.reg .pred p;\nsetp.ne.u32 p, %5, 0;\nmov.u32 %0, 0;\nmov.u32 %1, 0;\nmov.u32 %2, 0;\nmov.u32 %3, 0;\n@p ld.global.nc.v4.u32 {%0,%1,%2,%3}, [%4];\n}"
                 : "=r"(v.x), "=r"(v.y), "=r"(v.z), "=r"(v.w) : "l"(p), "r"((uint32_t)c));
    return v;
}
__device__ __forceinline__ uint32_t ldnc32(const void* p) { uint32_t v; asm volatile("ld.global.nc.u32 %0, [%1];" : "=r"(v) : "l"(p)); return v; }
__device__ __forceinline__ uint32_t ldnc16(const void* p) { uint32_t v; asm volatile("ld.global.nc.u16 %0, [%1];" : "=r"(v) : "l"(p)); return v; }
__device__ __forceinline__ unsigned int ld_epoch(const unsigned int* p) { unsigned int v; asm volatile("ld.relaxed.gpu.global.u32 %0, [%1];" : "=r"(v) : "l"(p)); return v; }
__device__ __forceinline__ void put4(uint4* p, float a, float b, float c, float d, uint32_t tag) {
    st128(p, make_uint4((__float_as_uint(a) & ~3u) | tag, __float_as_uint(b), __float_as_uint(c), __float_as_uint(d)));
}
__device__ __forceinline__ float4 as_f4(uint4 v) {
    return make_float4(__uint_as_float(v.x & ~3u), __uint_as_float(v.y), __uint_as_float(v.z), __uint_as_float(v.w));
}
__device__ __forceinline__ void add4(float4& a, const float4& b) { a.x += b.x; a.y += b.y; a.z += b.z; a.w += b.w; }
__device__ __forceinline__ float4 get4(const uint4* p, bool act, uint32_t tag) {
    uint4 v = make_uint4(tag, 0, 0, 0);
    int it = 0;
#pragma unroll 1
    do { if (act) v = ld128(p); } while (!__all_sync(~0u, (v.x & 3u) == tag) && ++it < SPIN_LIMIT);
    return as_f4(v);
}
__device__ __forceinline__ float4 get4sum2(const uint4* p0, const uint4* p1, bool act1, uint32_t tag) {
    uint4 u, v = make_uint4(tag, 0, 0, 0);
    int it = 0;
#pragma unroll 1
    do { u = ld128(p0); if (act1) v = ld128(p1); } while (!__all_sync(~0u, (u.x & 3u) == tag && (v.x & 3u) == tag) && ++it < SPIN_LIMIT);
    float4 a = as_f4(u);
    add4(a, make_float4(__uint_as_float(v.x & ~3u), __uint_as_float(v.y), __uint_as_float(v.z), __uint_as_float(v.w)));
    return a;
}

__device__ __forceinline__ uint2 ld64(const uint2* p) { uint2 v; asm volatile("{\n.reg .b64 t;\nld.relaxed.gpu.global.b64 t, [%2];\nmov.b64 {%0,%1}, t;\n}" : "=r"(v.x), "=r"(v.y) : "l"(p) : "memory"); return v; }
__device__ __forceinline__ void st64(uint2* p, uint32_t x, uint32_t y) { asm volatile("{\n.reg .b64 t;\nmov.b64 t, {%1,%2};\nst.relaxed.gpu.global.b64 [%0], t;\n}" ::"l"(p), "r"(x), "r"(y) : "memory"); }
__device__ __forceinline__ uint32_t pack_bf16(float lo, float hi);
__device__ __forceinline__ void put2(uint2* p, float a, float b, float c, float d, uint32_t par) { st64(p, (pack_bf16(a, b) & ~1u) | par, pack_bf16(c, d)); }
__device__ __forceinline__ float4 as_f4(uint2 v) {
    return make_float4(__uint_as_float(v.x << 16), __uint_as_float(v.x & 0xffff0000u), __uint_as_float(v.y << 16), __uint_as_float(v.y & 0xffff0000u));
}
__device__ __forceinline__ float4 get4sum4(const uint4* p0, int stride, uint32_t tag) {
    uint4 u0, u1, u2, u3;
    int it = 0;
#pragma unroll 1
    do { u0 = ld128(p0); u1 = ld128(p0 + stride); u2 = ld128(p0 + 2 * stride); u3 = ld128(p0 + 3 * stride); }
    while (!__all_sync(~0u, ((u0.x ^ tag) & 3u) == 0 && ((u1.x ^ tag) & 3u) == 0 && ((u2.x ^ tag) & 3u) == 0 && ((u3.x ^ tag) & 3u) == 0) && ++it < SPIN_LIMIT);
    float4 a = as_f4(u0), b = as_f4(u2);
    add4(a, as_f4(u1));
    add4(b, as_f4(u3));
    add4(a, b);
    return a;
}
__device__ __forceinline__ uint32_t pack_bf16(float lo, float hi) {
    uint32_t r;
    asm("cvt.rn.bf16x2.f32 %0, %1, %2;" : "=r"(r) : "f"(hi), "f"(lo));
    return r;
}
__device__ __forceinline__ float bf_lo(uint32_t u) { return __uint_as_float(u << 16); }
__device__ __forceinline__ float bf_hi(uint32_t u) { return __uint_as_float(u & 0xffff0000u); }
__device__ __forceinline__ float ex2(float x) { float y; asm("ex2.approx.ftz.f32 %0, %1;" : "=f"(y) : "f"(x)); return y; }

__device__ __forceinline__ void ldsm4(uint32_t (&r)[4], uint32_t addr) {
    asm volatile("ldmatrix.sync.aligned.m8n8.x4.shared.b16 {%0,%1,%2,%3}, [%4];" : "=r"(r[0]), "=r"(r[1]), "=r"(r[2]), "=r"(r[3]) : "r"(addr) : "memory");
}
__device__ __forceinline__ void ldsm4t(uint32_t (&r)[4], uint32_t addr) {
    asm volatile("ldmatrix.sync.aligned.m8n8.x4.trans.shared.b16 {%0,%1,%2,%3}, [%4];" : "=r"(r[0]), "=r"(r[1]), "=r"(r[2]), "=r"(r[3]) : "r"(addr) : "memory");
}
__device__ __forceinline__ void stsm4t(uint32_t addr, uint32_t r0, uint32_t r1, uint32_t r2, uint32_t r3) {
    asm volatile("stmatrix.sync.aligned.m8n8.x4.trans.shared.b16 [%0], {%1,%2,%3,%4};" ::"r"(addr), "r"(r0), "r"(r1), "r"(r2), "r"(r3) : "memory");
}
__device__ __forceinline__ void mma16816(float (&d)[4], const uint32_t (&a)[4], uint32_t b0, uint32_t b1) {
    asm volatile("mma.sync.aligned.m16n8k16.row.col.f32.bf16.bf16.f32 {%0,%1,%2,%3}, {%4,%5,%6,%7}, {%8,%9}, {%0,%1,%2,%3};"
                 : "+f"(d[0]), "+f"(d[1]), "+f"(d[2]), "+f"(d[3]) : "r"(a[0]), "r"(a[1]), "r"(a[2]), "r"(a[3]), "r"(b0), "r"(b1));
}
__device__ __forceinline__ void sts32(uint32_t a, uint32_t v) { asm volatile("st.shared.b32 [%0], %1;" ::"r"(a), "r"(v) : "memory"); }
__device__ __forceinline__ void sts16(uint32_t a, float v) {
    __nv_bfloat16 h = __float2bfloat16_rn(v);
    asm volatile("st.shared.b16 [%0], %1;" ::"r"(a), "h"(*reinterpret_cast<unsigned short*>(&h)) : "memory");
}
__device__ __forceinline__ void stsf(uint32_t a, float v) { asm volatile("st.shared.f32 [%0], %1;" ::"r"(a), "f"(v) : "memory"); }
__device__ __forceinline__ void stsf4(uint32_t a, float4 v) { asm volatile("st.shared.v4.f32 [%0], {%1,%2,%3,%4};" ::"r"(a), "f"(v.x), "f"(v.y), "f"(v.z), "f"(v.w) : "memory"); }
__device__ __forceinline__ uint32_t lds32(uint32_t a) { uint32_t v; asm volatile("ld.shared.b32 %0, [%1];" : "=r"(v) : "r"(a) : "memory"); return v; }
__device__ __forceinline__ float ldsf(uint32_t a) { float v; asm volatile("ld.shared.f32 %0, [%1];" : "=f"(v) : "r"(a) : "memory"); return v; }
__device__ __forceinline__ float2 ldsf2(uint32_t a) { float2 v; asm volatile("ld.shared.v2.f32 {%0,%1}, [%2];" : "=f"(v.x), "=f"(v.y) : "r"(a) : "memory"); return v; }
__device__ __forceinline__ float4 ldsf4(uint32_t a) { float4 v; asm volatile("ld.shared.v4.f32 {%0,%1,%2,%3}, [%4];" : "=f"(v.x), "=f"(v.y), "=f"(v.z), "=f"(v.w) : "r"(a) : "memory"); return v; }
__device__ __forceinline__ uint4 lds128(uint32_t a) { uint4 v; asm volatile("ld.shared.v4.b32 {%0,%1,%2,%3}, [%4];" : "=r"(v.x), "=r"(v.y), "=r"(v.z), "=r"(v.w) : "r"(a) : "memory"); return v; }

__device__ __forceinline__ void tma2d(uint32_t dst, const CUtensorMap* m, int c0, int c1, uint32_t bar, uint32_t bytes, uint64_t pol) {
    asm volatile("{\n.reg .pred p;\nelect.sync _|p, 0xffffffff;\n"
                 "@p mbarrier.arrive.expect_tx.shared::cta.b64 _, [%2], %6;\n"
                 "@p cp.async.bulk.tensor.2d.shared::cluster.global.mbarrier::complete_tx::bytes.L2::cache_hint [%0], [%1, {%3, %4}], [%2], %5;\n}"
                 ::"r"(dst), "l"(m), "r"(bar), "r"(c0), "r"(c1), "l"(pol), "r"(bytes) : "memory");
}
__device__ __forceinline__ void tma3d(uint32_t dst, const CUtensorMap* m, int c0, int c1, int c2, uint32_t bar, uint32_t bytes, uint64_t pol) {
    asm volatile("{\n.reg .pred p;\nelect.sync _|p, 0xffffffff;\n"
                 "@p mbarrier.arrive.expect_tx.shared::cta.b64 _, [%2], %7;\n"
                 "@p cp.async.bulk.tensor.3d.shared::cluster.global.mbarrier::complete_tx::bytes.L2::cache_hint [%0], [%1, {%3, %4, %5}], [%2], %6;\n}"
                 ::"r"(dst), "l"(m), "r"(bar), "r"(c0), "r"(c1), "r"(c2), "l"(pol), "r"(bytes) : "memory");
}
__device__ __forceinline__ void tma2d_na(uint32_t dst, const CUtensorMap* m, int c0, int c1, uint32_t bar, uint64_t pol) {
    asm volatile("{\n.reg .pred p;\nelect.sync _|p, 0xffffffff;\n"
                 "@p cp.async.bulk.tensor.2d.shared::cluster.global.mbarrier::complete_tx::bytes.L2::cache_hint [%0], [%1, {%3, %4}], [%2], %5;\n}"
                 ::"r"(dst), "l"(m), "r"(bar), "r"(c0), "r"(c1), "l"(pol) : "memory");
}
__device__ __forceinline__ uint32_t mapa(uint32_t addr, uint32_t rank) {
    uint32_t r;
    asm("mapa.shared::cluster.u32 %0, %1, %2;" : "=r"(r) : "r"(addr), "r"(rank));
    return r;
}
__device__ __forceinline__ void st_async4(uint32_t raddr, uint32_t a, uint32_t b, uint32_t c, uint32_t d, uint32_t rbar) {
    asm volatile("st.async.weak.shared::cluster.mbarrier::complete_tx::bytes.v4.b32 [%0], {%1,%2,%3,%4}, [%5];" ::"r"(raddr), "r"(a), "r"(b), "r"(c), "r"(d), "r"(rbar) : "memory");
}
__device__ __forceinline__ void st_async2(uint32_t raddr, float a, float b, uint32_t rbar) {
    asm volatile("st.async.weak.shared::cluster.mbarrier::complete_tx::bytes.v2.f32 [%0], {%1,%2}, [%3];" ::"r"(raddr), "f"(a), "f"(b), "r"(rbar) : "memory");
}
__device__ __forceinline__ void tma3d_mc(uint32_t dst, const CUtensorMap* m, int c0, int c1, int c2, uint32_t bar, uint32_t bytes) {
    asm volatile("{\n.reg .pred p;\nelect.sync _|p, 0xffffffff;\n"
                 "@p mbarrier.arrive.expect_tx.shared::cta.b64 _, [%2], %6;\n"
                 "@p cp.async.bulk.tensor.3d.shared::cluster.global.mbarrier::complete_tx::bytes.multicast::cluster [%0], [%1, {%3, %4, %5}], [%2], %7;\n}"
                 ::"r"(dst), "l"(m), "r"(bar), "r"(c0), "r"(c1), "r"(c2), "r"(bytes), "h"((unsigned short)3) : "memory");
}
__device__ __forceinline__ void bulk_s2g(void* dst, uint32_t src, uint32_t bytes) {
    asm volatile("cp.async.bulk.global.shared::cta.bulk_group [%0], [%1], %2;" ::"l"(dst), "r"(src), "r"(bytes) : "memory");
}
__device__ __forceinline__ void prefetch_map(const CUtensorMap* m) { asm volatile("prefetch.tensormap [%0];" ::"l"(m) : "memory"); }

constexpr uint32_t DESC_HI = 64u | (1u << 30);
__device__ __forceinline__ constexpr uint32_t desc_lo(uint32_t addr) { return ((addr & 0x3FFFF) >> 4) | (1u << 16); }
__device__ __forceinline__ void wg_fence() { asm volatile("wgmma.fence.sync.aligned;" ::: "memory"); }
__device__ __forceinline__ void wg_commit() { asm volatile("wgmma.commit_group.sync.aligned;" ::: "memory"); }
__device__ __forceinline__ void wg_wait0() { asm volatile("wgmma.wait_group.sync.aligned 0;" ::: "memory"); }
template <int TA>
__device__ __forceinline__ void wgmma_n32(float (&d)[16], uint32_t alo, uint32_t blo, int scale_d) {
    asm volatile("{\n.reg .pred p;\n.reg .b64 da, db;\nsetp.ne.b32 p, %18, 0;\nmov.b64 da, {%16, %20};\nmov.b64 db, {%17, %20};\n"
                 "wgmma.mma_async.sync.aligned.m64n32k16.f32.bf16.bf16 "
                 "{%0,%1,%2,%3,%4,%5,%6,%7,%8,%9,%10,%11,%12,%13,%14,%15}, da, db, p, 1, 1, %19, 0;\n}"
                 : "+f"(d[0]), "+f"(d[1]), "+f"(d[2]), "+f"(d[3]), "+f"(d[4]), "+f"(d[5]), "+f"(d[6]), "+f"(d[7]),
                   "+f"(d[8]), "+f"(d[9]), "+f"(d[10]), "+f"(d[11]), "+f"(d[12]), "+f"(d[13]), "+f"(d[14]), "+f"(d[15])
                 : "r"(alo), "r"(blo), "r"(scale_d), "n"(TA), "n"(DESC_HI));
}
template <int N>
__device__ __forceinline__ void reg_fence(float (&d)[N]) {
#pragma unroll
    for (int i = 0; i < N; i++) asm volatile("" : "+f"(d[i])::"memory");
}

#define TS(slot)
#define TS0(slot)

__device__ __forceinline__ unsigned int gtimer_lo() {
    unsigned long long t;
    asm volatile("mov.u64 %0, %globaltimer;" : "=l"(t));
    return (unsigned int)t;
}
__device__ __forceinline__ unsigned int clock32() { unsigned int c; asm volatile("mov.u32 %0, %clock;" : "=r"(c)); return c; }
__device__ __forceinline__ void spin(int cycles) {
    if (cycles <= 0) return;
    const unsigned int t0 = clock32();
#pragma unroll 1
    while (clock32() - t0 < (unsigned int)cycles) {}
}
__device__ __forceinline__ unsigned int ld_cnt(const unsigned int* p) {
    unsigned int v;
    asm volatile("ld.relaxed.gpu.global.u32 %0, [%1];" : "=r"(v) : "l"(p) : "memory");
    return v;
}
__device__ __forceinline__ void wait_cnt(const unsigned int* p, unsigned int target) {
    int it = 0;
#pragma unroll 1
    while ((int)(ld_cnt(p) - target) < 0) { if (++it > SPIN_LIMIT) break; }
}
__device__ __forceinline__ void red_cnt(unsigned int* p) { asm volatile("red.relaxed.gpu.global.add.u32 [%0], 1;" ::"l"(p) : "memory"); }

constexpr uint32_t SB0 = 1024;
__device__ __forceinline__ uint32_t smem_base() {
    extern __shared__ __align__(1024) uint8_t smem_dyn[];
    return smem_u32(smem_dyn);
}

__device__ __forceinline__ void gemv_y_load(uint32_t (&a)[8][4]) {
    const int lane = threadIdx.x & 31, warp = threadIdx.x >> 5;
    const int blk = lane >> 3, r8 = lane & 7;
    const int ch = (warp & 3) * 2 + (blk & 1);
    const uint32_t arow = smem_base() + OFF_Y + (warp >> 2) * 16384 + ((blk >> 1) * 8 + r8) * 128 + ((ch ^ r8) << 4);
#pragma unroll
    for (int k = 0; k < 8; k++) ldsm4t(a[k], arow + k * 16 * 128);
}
__device__ __forceinline__ void gemv_y_put(const uint32_t (&a)[8][4], uint4* dst, uint32_t act, uint32_t tag) {
    const int lane = threadIdx.x & 31, warp = threadIdx.x >> 5;
    const uint32_t brow = act + (lane & 3) * 272 + (lane >> 3) * 16;
    uint32_t b[4][4];
#pragma unroll
    for (int k = 0; k < 4; k++) ldsm4(b[k], brow + k * 64);
    float d[4] = {0.f, 0.f, 0.f, 0.f}, e[4] = {0.f, 0.f, 0.f, 0.f};
#pragma unroll
    for (int k = 0; k < 4; k++) {
        mma16816(d, a[2 * k], b[k][0], b[k][1]);
        mma16816(e, a[2 * k + 1], b[k][2], b[k][3]);
    }
    const uint32_t x = (__float_as_uint(d[0] + e[0]) & ~3u) | tag;
    const float y = d[1] + e[1], z = d[2] + e[2], w = d[3] + e[3];
    if ((lane & 3) < 2) st128(dst + warp * 16 + (lane >> 2) * 2 + (lane & 3), make_uint4(x, __float_as_uint(y), __float_as_uint(z), __float_as_uint(w)));
}

__device__ __forceinline__ void gemv_512x16(float (&d)[4], uint32_t tile, uint32_t act, int k0, int nk2, int lane) {
    const int blk = lane >> 3, r8 = lane & 7;
    uint32_t arow = tile + (k0 + (blk >> 1) * 8 + r8) * 32 + (((blk & 1) ^ ((r8 >> 2) & 1)) << 4);
    uint32_t brow = act + (r8 & 3) * 1040 + (k0 + blk * 8) * 2;
#pragma unroll 2
    for (int k2 = 0; k2 < nk2; k2++) {
        uint32_t b[4], a0[4], a1[4];
        ldsm4(b, brow);
        ldsm4t(a0, arow);
        ldsm4t(a1, arow + 512);
        mma16816(d, a0, b[0], b[1]);
        mma16816(d, a1, b[2], b[3]);
        brow += 64;
        arow += 1024;
    }
}

__device__ __noinline__ float4 reduce16(const uint2* base, int n, uint32_t par, int delay) {
    const int t = threadIdx.x, lane = t & 31, warp = t >> 5;
    const uint32_t SCR = smem_base() + OFF_SCR;
    const int pp = t >> 2;
    const uint2* p0 = base + (size_t)pp * 512 + blockIdx.x * 4 + (t & 3);
    const bool act1 = pp + 64 < n;
    spin(delay);
    uint2 u, v = make_uint2(par, 0);
    int it = 0;
#pragma unroll 1
    do { u = ld64(p0); if (act1) v = ld64(p0 + 64 * 512); } while (!__all_sync(~0u, (((u.x ^ par) | (v.x ^ par)) & 1u) == 0) && ++it < SPIN_LIMIT);
    float4 a = as_f4(u);
    if (act1) add4(a, as_f4(v));
#pragma unroll
    for (int of = 4; of <= 16; of <<= 1) {
        a.x += __shfl_xor_sync(~0u, a.x, of); a.y += __shfl_xor_sync(~0u, a.y, of);
        a.z += __shfl_xor_sync(~0u, a.z, of); a.w += __shfl_xor_sync(~0u, a.w, of);
    }
    if (lane < 4) stsf4(SCR + (warp * 4 + lane) * 16, a);
    bar_main();
    float4 r = make_float4(0.f, 0.f, 0.f, 0.f);
    if (t < 4) {
#pragma unroll
        for (int w = 0; w < 8; w++) add4(r, ldsf4(SCR + (w * 4 + t) * 16));
    }
    return r;
}
__device__ __forceinline__ void sts_frag(uint32_t base, uint32_t stride, int m, int b0, float x, float y, float z, float w) {
    const uint32_t a = base + b0 * stride + m * 2;
    sts16(a, x); sts16(a + stride, y); sts16(a + 16, z); sts16(a + stride + 16, w);
}

__global__ void __cluster_dims__(2, 1, 1) __launch_bounds__(NTHREADS, 1) fused_kernel(const __grid_constant__ Params p) {
    extern __shared__ __align__(1024) uint8_t smem[];
    const uint32_t sb = smem_base();
    const int t = threadIdx.x, lane = t & 31;
    const int warp = __shfl_sync(0xffffffffu, t >> 5, 0);
    const int i = blockIdx.x;
    const int hh = i >> 2, jj = i & 3;
    const int bb = i >> 5, chunk = i & 31;
    const uint32_t rank = i & 1;
    auto BAR = [&](int k) { return sb + OFF_BAR + k * 8; };
    const uint32_t MISC = sb + OFF_MISC;

    if (warp == 8) {
        if (lane == 0) {
            TS(0);
            prefetch_map(&p.wmoda);
            prefetch_map(&p.wq);
            mbar_init(BAR(B_WA), 1);
            mbar_init(BAR(0), 1);
            asm volatile("fence.mbarrier_init.release.cluster;" ::: "memory");
            fence_async_smem();
            mbar_expect_tx(BAR(B_WA), 8192);
        }
        __syncwarp();
        uint64_t pol;
        asm volatile("createpolicy.fractional.L2::evict_first.b64 %0, 1.0;" : "=l"(pol));
        tma2d_na(sb + OFF_Z, &p.wmoda, 16 * hh, jj * 128, BAR(B_WA), pol);
        tma2d_na(sb + OFF_Z + 4096, &p.wmoda, 512 + 16 * hh, jj * 128, BAR(B_WA), pol);
        tma2d(sb + OFF_Y, &p.wq, hh * 128, jj * 128, BAR(0), 8192, pol);
        unsigned int due = gtimer_lo() + DT_0;
        TS(56);
        if (lane == 0) {
            if ((sb & 0xFFFFFFu) != SB0) __trap();
#pragma unroll
            for (int k = 1; k < 4; k++) mbar_init(BAR(k), 1);
            asm volatile("fence.mbarrier_init.release.cluster;" ::: "memory");
            fence_async_smem();
        }
        __syncwarp();
        asm volatile("bar.arrive 4, 320;" ::: "memory");
        auto pace_dt = [&](int it, unsigned int dt) {
            if (it >= WINDOW) mbar_wait(BAR(0) + (it - WINDOW) * 8);
            int spin_it = 0;
#pragma unroll 1
            while ((int)(gtimer_lo() - due) < 0 && ++spin_it < SPIN_LIMIT) {}
            due += dt;
        };
                auto pace = [&](int it) { pace_dt(it, it < B_KV ? DT_F : (it < B_W1 ? DT_T : DT_T2)); };
        auto tile128 = [&](const CUtensorMap* m, int first, uint32_t dst, int k0) {
#pragma unroll 1
            for (int k = k0; k < 4; k++) {
                pace(first + k);
                tma2d(dst + k * 8192, m, hh * 128 + (k >> 1) * 64, jj * 128 + (k & 1) * 64, BAR(0) + (first + k) * 8, 8192, pol);
            }
        };
        tile128(&p.wq, B_WQ, sb + OFF_Y, 1);
        asm volatile("bar.sync 5, 320;" ::: "memory");
        TS(57);
        tile128(&p.wuk, B_WUK, sb + OFF_X, 0);
        TS(61);
#pragma unroll 1
        for (int s = 0; s < 16; s++) {
            pace_dt(B_KV + s, mbar_test(BAR(B_QABS)) ? DT_S : DT_F);
            tma2d(sb + OFF_KV + s * 8192, &p.kv, (s & 7) * 64, bb * 4096 + chunk * 128 + (s >> 3) * 64, BAR(B_KV) + s * 8, 8192, pol);
        }
        if (lane == 0) sts32(MISC + 232, due);
        TS(43);
        mbar_wait(BAR(B_YFREE));
        auto mod_items = [&]() {
#pragma unroll 1
            for (int k = 0; k < 2; k++) {
                pace(B_MOD + k);
                tma2d(sb + OFF_Z + k * 8192, &p.wmod, 1024 + 16 * i, k * 256, BAR(B_MOD) + k * 8, 8192, pol);
            }
        };
        mod_items();
        tile128(&p.wuv, B_WUV, sb + OFF_Y, 0);
        mbar_wait(BAR(B_XFREE));
#pragma unroll 1
        for (int k = 0; k < 4; k++) {
            pace(B_WO + k);
            tma3d(sb + OFF_X + k * 8192, &p.wo, 0, hh * 128 + jj * 32, k * 2, BAR(B_WO) + k * 8, 8192, pol);
        }
        if (i < NFFN) {
            mbar_wait(BAR(B_G4));
            due = gtimer_lo();
            mbar_wait(BAR(B_ZFREE));
#pragma unroll 1
            for (int k = 0; k < 2; k++) {
                pace(B_W1 + k);
                tma2d(sb + OFF_Z + k * 8192, &p.w1, 16 * i, k * 256, BAR(B_W1) + k * 8, 8192, pol);
            }
            mbar_wait(BAR(B_KV0FREE));
#pragma unroll 1
            for (int k = 0; k < 2; k++) {
                pace(B_W2 + k);
                tma3d(sb + OFF_W2 + k * 8192, &p.w2, 0, 16 * i, k * 4, BAR(B_W2) + k * 8, 8192, pol);
            }
        }
        TS(40);
    } else if (warp == 9) {
        unsigned int ep = 0;
        if (lane == 0) {
            ep = ld_epoch(&g_sync[(i % NSYNC) * 32]);
            mbar_init(BAR(B_YFREE), 8);
            mbar_init(BAR(B_XFREE), 4);
            mbar_init(BAR(B_KV0FREE), 8);
            mbar_init(BAR(B_EP), 1);
            mbar_init(BAR(B_PEER0), 8);
            mbar_init(BAR(B_XCH), 1);
            mbar_init(BAR(B_G4), 1);
            mbar_init(BAR(B_XST), 2);
            mbar_expect_tx(BAR(B_XCH), 16384);
            mbar_expect_tx(BAR(B_XST), 128);
            asm volatile("fence.mbarrier_init.release.cluster;" ::: "memory");
        }
        __syncwarp();
        asm volatile("bar.arrive 5, 320;" ::: "memory");
        asm volatile("bar.arrive 4, 320;" ::: "memory");
        if (lane < 9) prefetch_map(&p.kv + lane);
        const uint4 z = make_uint4(0, 0, 0, 0);
        st128(&g_H[i * 32 + lane], z);
#pragma unroll
        for (int k = 0; k < 4; k++) st128(&g_Q[i * 128 + k * 32 + lane], z);
        uint32_t xr = 0;
        if (lane < 16) {
            const int V = i * 4 + (lane >> 2), e = lane & 3;
            const int m = (V >> 4) * 16 + ((V & 15) >> 1) + (e >> 1) * 8, b = (V & 1) * 2 + (e & 1);
            xr = ldnc16(p.x + b * 512 + m);
        }
        TS(35);
        asm volatile("bar.sync 6, 288;" ::: "memory");
        TS(30);
        __syncwarp();
        if (lane == 0) {
            sts32(MISC + 224, ep);
            sts32(MISC + 236, 0);
            mbar_arrive(BAR(B_EP));
        }
        TS(31);
        mbar_wait(BAR(B_EP));
        ep = lds32(MISC + 224);
        const uint32_t tag = 1u + 2u * (ep & 1u);
        if (lane < 16) stsf(MISC + 32 + lane * 4, __uint_as_float(xr << 16));
        mbar_wait(BAR(B_P3));
        wait_cnt(&g_sync[(4 + (i & 3)) * 32 + 1], (ep + 1u) * 128u);
        __syncwarp();
        tma3d_mc(sb + OFF_X + rank * 16384, &p.qabs, 0, bb * 32, rank * 4, BAR(B_QABS), 32768);
        TS(41);
#pragma unroll 1
        for (int k = 0; k < 4; k++) st128(&g_C[i * 128 + k * 32 + lane], z);
        if (lane < 16) st128(&g_M[i * 16 + lane], z);
        {
            const uint32_t inv = ep & 1u;
            const uint4 zi = make_uint4(inv, 0, inv, 0);
            if (lane < 8) st128(reinterpret_cast<uint4*>(&g_X1[i * 16]) + lane, zi);
#pragma unroll 1
            for (int k = 0; k < 8; k++) {
                st128(reinterpret_cast<uint4*>(&g_O[i * 512]) + k * 32 + lane, zi);
                if (i < NFFN) st128(reinterpret_cast<uint4*>(&g_F[i * 512]) + k * 32 + lane, zi);
                spin(100);
            }
        }
        __syncwarp();
        if (lane == 0) mbar_arrive(BAR(B_CLR2));
        TS(44);
        mbar_wait_n(BAR(B_MOD), 2);
        float d[4] = {0.f, 0.f, 0.f, 0.f};
        gemv_512x16(d, sb + OFF_Z, sb + OFF_S, 0, 16, lane);
        __syncwarp();
        if (lane == 0) mbar_arrive(BAR(B_ZFREE));
        if ((lane & 3) < 2) put4(&g_M[i * 16 + (lane >> 2) * 2 + (lane & 3)], d[0], d[1], d[2], d[3], tag);
        __syncwarp();
        if (lane == 0 && i >= 32 && i < 96) red_cnt(&g_sync[4 * 32 + 2]);
        TS(42);
        {
            const float4 v = get4(&g_M[((lane >> 2) & 1) * 3 * 512 + i * 4 + (lane & 3)], lane < 8, tag);
            if (lane < 8) stsf4(MISC + 96 + lane * 16, v);
        }
        __syncwarp();
        if (lane == 0) {
            if (i < NFFN) {
                wait_cnt(&g_sync[4 * 32 + 2], (ep + 1u) * 64u);
                mbar_wait(BAR(B_KV0FREE));
                asm volatile("fence.proxy.async.global;" ::: "memory");
                mbar_expect_tx(BAR(B_MODV), 16384);
                asm volatile("cp.async.bulk.shared::cluster.global.mbarrier::complete_tx::bytes [%0], [%1], %2, [%3];"
                             ::"r"(sb + OFF_SBCB), "l"(&g_M[512]), "r"(16384), "r"(BAR(B_MODV)) : "memory");
            } else {
                mbar_arrive(BAR(B_MODV));
            }
            TS(45);
        }
    } else {
        const uint32_t ACT = sb + OFF_ACT, ACTB = sb + OFF_ACT + 1152, RED = sb + OFF_RED;
        const int g = lane >> 2, q = lane & 3;
        const int vrr = (lane & 15) >> 1, vb0 = (lane & 1) * 2;
        uint32_t cw[4];
        uint4 xv[2];
        uint32_t xh[4];
        TS0(32);
        {
            const uint4* xp = reinterpret_cast<const uint4*>(p.x + (warp & 3) * 512 + lane * 16);
            xv[0] = ldnc128_if(xp, warp < 4);
            xv[1] = ldnc128_if(xp + 1, warp < 4);
            const __nv_bfloat16* xq = p.x + vb0 * 512 + jj * 128 + warp * 16 + vrr;
            xh[0] = ldnc16(xq); xh[1] = ldnc16(xq + 512); xh[2] = ldnc16(xq + 8); xh[3] = ldnc16(xq + 520);
        }
#pragma unroll
        for (int b = 0; b < 4; b++) cw[b] = ldnc32(p.c + b * 512 + 2 * t);
        if (lane == 0) {
#pragma unroll
            for (int k = 0; k < 5; k++) {
                int idx = 4 + warp * 5 + k;
                if (idx >= B_YFREE) idx = (idx == 39) ? B_ZFREE : (idx == 40 ? B_P3 : (idx == 41 ? B_CLR2 : B_MODV));
                mbar_init(BAR(0) + idx * 8, 1);
            }
            asm volatile("fence.mbarrier_init.release.cluster;" ::: "memory");
        }
        __syncwarp();
        asm volatile("bar.arrive 5, 320;" ::: "memory");
        asm volatile("bar.arrive 6, 288;" ::: "memory");
        TS(48 + warp);
        asm volatile("bar.sync 4, 320;" ::: "memory");
        TS0(29);

#pragma unroll
        for (int b = 0; b < 4; b++) {
            const float c0 = bf_lo(cw[b]), c1 = bf_hi(cw[b]);
            sts32(sb + OFF_S + b * 1040 + t * 4, pack_bf16(__fdividef(c0, 1.f + __expf(-c0)), __fdividef(c1, 1.f + __expf(-c1))));
        }
        if (warp < 4) {
            const uint32_t u[8] = {xv[0].x, xv[0].y, xv[0].z, xv[0].w, xv[1].x, xv[1].y, xv[1].z, xv[1].w};
            float s = 0.f, ss = 0.f;
#pragma unroll
            for (int k = 0; k < 8; k++) s += bf_lo(u[k]) + bf_hi(u[k]);
#pragma unroll
            for (int o = 16; o; o >>= 1) s += __shfl_xor_sync(~0u, s, o);
            const float mean = s * (1.f / 512.f);
#pragma unroll
            for (int k = 0; k < 8; k++) { const float d0 = bf_lo(u[k]) - mean, d1 = bf_hi(u[k]) - mean; ss += d0 * d0 + d1 * d1; }
#pragma unroll
            for (int o = 16; o; o >>= 1) ss += __shfl_xor_sync(~0u, ss, o);
            if (lane == 0) { stsf(MISC + warp * 8, mean); stsf(MISC + warp * 8 + 4, rsqrtf(ss * (1.f / 512.f) + 1e-5f)); }
        }
        bar_main();
        mbar_wait(BAR(B_EP));
        const unsigned int ep = lds32(MISC + 224);
        const uint32_t tag = 1u + 2u * (ep & 1u);
        const uint32_t par = (ep & 1u) ^ 1u;
        if (warp < 2) {
            mbar_wait(BAR(B_WA));
            TS0(26);
            float d[4] = {0.f, 0.f, 0.f, 0.f};
            gemv_512x16(d, sb + OFF_Z + warp * 4096 - jj * 4096, sb + OFF_S, jj * 128, 4, lane);
            if (q < 2) put4(&g_H[i * 32 + warp * 16 + g * 2 + q], d[0], d[1], d[2], d[3], tag);
        }
        TS0(1);
        mbar_wait_n(BAR(B_WQ), 4);
        uint32_t afr[8][4];
        gemv_y_load(afr);
        TS0(3);
        {
            const float4 a = get4sum4(&g_H[(4 * (8 * jj + warp)) * 32 + lane], 32, tag);
            const float cx = __shfl_down_sync(~0u, a.x, 16), cy = __shfl_down_sync(~0u, a.y, 16);
            const float cz = __shfl_down_sync(~0u, a.z, 16), cwv = __shfl_down_sync(~0u, a.w, 16);
            if (lane < 16) {
                const float2 s0 = ldsf2(MISC + vb0 * 8), s1 = ldsf2(MISC + vb0 * 8 + 8);
                sts_frag(ACT, 272, warp * 16 + vrr, vb0,
                         (__uint_as_float(xh[0] << 16) - s0.x) * s0.y * (1.f + cx) + a.x,
                         (__uint_as_float(xh[1] << 16) - s1.x) * s1.y * (1.f + cy) + a.y,
                         (__uint_as_float(xh[2] << 16) - s0.x) * s0.y * (1.f + cz) + a.z,
                         (__uint_as_float(xh[3] << 16) - s1.x) * s1.y * (1.f + cwv) + a.w);
            }
        }
        bar_main();
        TS0(2);
        gemv_y_put(afr, &g_Q[i * 128], ACT, tag);
        __syncwarp();
        if (lane == 0) mbar_arrive(BAR(B_YFREE));
        mbar_wait_n(BAR(B_WUK), 4);
        TS0(5);
        if (warp < 4) {
            const float4 a = get4sum4(&g_Q[hh * 4 * 128 + t], 128, tag);
            sts_frag(ACTB, 272, (t >> 4) * 16 + vrr, vb0, a.x, a.y, a.z, a.w);
        }
        bar_main();
        TS0(4);
        {
            float d[4] = {0.f, 0.f, 0.f, 0.f};
            const int blk = lane >> 3, r8 = lane & 7;
            const uint32_t arow = sb + OFF_X + (warp * 16 + (blk & 1) * 8 + r8) * 128;
            const uint32_t brow = ACTB + (r8 & 3) * 272 + blk * 16;
            uint32_t a[8][4], b[4][4];
#pragma unroll
            for (int k = 0; k < 8; k++) ldsm4(a[k], arow + (k >> 2) * 16384 + ((((k & 3) * 2 + (blk >> 1)) ^ r8) << 4));
#pragma unroll
            for (int k = 0; k < 4; k++) ldsm4(b[k], brow + k * 64);
            float e[4] = {0.f, 0.f, 0.f, 0.f};
#pragma unroll
            for (int k = 0; k < 4; k++) {
                mma16816(d, a[2 * k], b[k][0], b[k][1]);
                mma16816(e, a[2 * k + 1], b[k][2], b[k][3]);
            }
            d[0] += e[0]; d[1] += e[1]; d[2] += e[2]; d[3] += e[3];
            const float sc = 0.08838834764831845f * 1.4426950408889634f;
            if (q < 2) sts_frag(RED, 256, warp * 16 + g, 2 * q, d[0] * sc, d[1] * sc, d[2] * sc, d[3] * sc);
            fence_async_smem();
            bar_main();
            if (t == 0) {
#pragma unroll 1
                for (int b = 0; b < 4; b++) bulk_s2g(&g_qabs[(b * 32 + hh) * 512 + jj * 128], RED + b * 256, 256);
                asm volatile("cp.async.bulk.commit_group;" ::: "memory");
                asm volatile("cp.async.bulk.wait_group 0;" ::: "memory");
#pragma unroll
                for (int r = 0; r < 4; r++) red_cnt(&g_sync[(4 + r) * 32 + 1]);
                mbar_arrive(BAR(B_P3));
            }
            TS0(6);
        }
        const int wg = warp >> 2, wq = warp & 3;
        {
            const uint32_t MX = RED;
            const uint32_t LRED = RED + 512;
            const uint32_t OST = ACTB + 128, PST = ACTB;
            const uint32_t ALPHA = RED + 1536, MRUN = RED + 1664;
            float o[4][16];
            float lsum[8];
#pragma unroll
            for (int k = 0; k < 8; k++) lsum[k] = 0.f;
            if (t < 32) stsf(MRUN + t * 4, -INFINITY);
            mbar_wait(BAR(B_QABS));
            TS0(7);
            float s[16];
            auto qk = [&](int c0, int c1) {
                uint32_t da = desc_lo(SB0 + OFF_KV) + wg * (65536 >> 4) + c0 * (8192 >> 4), db = desc_lo(SB0 + OFF_X) + c0 * (4096 >> 4);
#pragma unroll 1
                for (int cb = c0; cb < c1; cb++) {
                    mbar_wait(BAR(B_KV) + (wg * 8 + cb) * 8);
                    wg_fence();
#pragma unroll
                    for (int k = 0; k < 4; k++) wgmma_n32<0>(s, da + k * 2, db + k * 2, (cb | k) != 0);
                    wg_commit();
                    da += 8192 >> 4;
                    db += 4096 >> 4;
                }
            };
            if (wg == 1) qk(0, QK_EARLY);
#pragma unroll 1
            for (int tile = 0; tile < 2; tile++) {
                if (wg == tile) {
                    qk(tile == 0 ? 0 : QK_EARLY, 8);
                    wg_wait0();
                    reg_fence(s);
                    if (tile == 1) {
                        __syncwarp();
                        if (lane == 0) {
                            mbar_arrive(BAR(B_XFREE));
                            mbar_arrive(BAR(B_KV0FREE));
                            asm volatile("mbarrier.arrive.relaxed.cluster.shared::cluster.b64 _, [%0];" ::"r"(mapa(BAR(B_PEER0), rank ^ 1)) : "memory");
                        }
                    }
                    if (wq == 0) TS(8 + tile * 2);
                    float m[8];
#pragma unroll
                    for (int jb = 0; jb < 4; jb++) {
                        m[2 * jb] = fmaxf(s[4 * jb], s[4 * jb + 2]);
                        m[2 * jb + 1] = fmaxf(s[4 * jb + 1], s[4 * jb + 3]);
                    }
                    {
                        const bool u4 = lane & 16, u3 = lane & 8, u2 = lane & 4;
                        float h4[4], h2[2];
#pragma unroll
                        for (int k = 0; k < 4; k++) h4[k] = fmaxf(u4 ? m[k + 4] : m[k], __shfl_xor_sync(~0u, u4 ? m[k] : m[k + 4], 16));
#pragma unroll
                        for (int k = 0; k < 2; k++) h2[k] = fmaxf(u3 ? h4[k + 2] : h4[k], __shfl_xor_sync(~0u, u3 ? h4[k] : h4[k + 2], 8));
                        const float h1 = fmaxf(u2 ? h2[1] : h2[0], __shfl_xor_sync(~0u, u2 ? h2[0] : h2[1], 4));
                        stsf(MX + (wq * 32 + 8 * (g >> 1) + 2 * q + (g & 1)) * 4, h1);
                    }
                    if (tile == 0) asm volatile("bar.sync 2, 128;" ::: "memory"); else asm volatile("bar.sync 3, 128;" ::: "memory");
                    const float mold = ldsf(MRUN + tile * 128 + lane * 4);
                    const float mnew = fmaxf(fmaxf(fmaxf(ldsf(MX + lane * 4), ldsf(MX + 128 + lane * 4)), fmaxf(ldsf(MX + 256 + lane * 4), ldsf(MX + 384 + lane * 4))), mold);
                    uint32_t lo[4], hi[4];
#pragma unroll
                    for (int jb = 0; jb < 4; jb++) {
                        const float m0 = __shfl_sync(~0u, mnew, 8 * jb + 2 * q), m1 = __shfl_sync(~0u, mnew, 8 * jb + 2 * q + 1);
                        lo[jb] = pack_bf16(ex2(s[4 * jb] - m0), ex2(s[4 * jb + 1] - m1));
                        hi[jb] = pack_bf16(ex2(s[4 * jb + 2] - m0), ex2(s[4 * jb + 3] - m1));
                        lsum[2 * jb] = bf_lo(lo[jb]) + bf_lo(hi[jb]);
                        lsum[2 * jb + 1] = bf_hi(lo[jb]) + bf_hi(hi[jb]);
                    }
                    const uint32_t prow = sb + OFF_P + tile * 4096 + ((lane + 16 * rank) & 31) * 128;
                    stsm4t(prow + (((2 * wq) ^ (lane & 7)) << 4), lo[0], lo[1], lo[2], lo[3]);
                    stsm4t(prow + (((2 * wq + 1) ^ (lane & 7)) << 4), hi[0], hi[1], hi[2], hi[3]);
                    fence_async_smem();
                    if (wq == 0) { stsf(ALPHA + lane * 4, ex2(mold - mnew)); stsf(MRUN + (tile + 1) * 128 + lane * 4, mnew); }
                }
                bar_main();
                TS0(27 + tile);
                if (tile == 1) {
                    wg_wait0();
#pragma unroll
                    for (int mt = 0; mt < 4; mt++) reg_fence(o[mt]);
#pragma unroll
                    for (int jb = 0; jb < 4; jb++) {
                        const float2 a = ldsf2(ALPHA + ((8 * jb + 2 * q + 16 * rank) & 31) * 4);
#pragma unroll
                        for (int mt = 0; mt < 4; mt++) { o[mt][4 * jb] *= a.x; o[mt][4 * jb + 1] *= a.y; o[mt][4 * jb + 2] *= a.x; o[mt][4 * jb + 3] *= a.y; }
                    }
                }
                {
                    const uint32_t da = desc_lo(SB0 + OFF_KV) + tile * (65536 >> 4) + wg * (32768 >> 4), db = desc_lo(SB0 + OFF_P) + tile * (4096 >> 4);
                    wg_fence();
#pragma unroll
                    for (int mt = 0; mt < 4; mt++) {
#pragma unroll
                        for (int k = 0; k < 4; k++)
                            wgmma_n32<1>(o[mt], da + mt * (8192 >> 4) + k * (2048 >> 4), db + k * 2, tile | k);
                        wg_commit();
                    }
                }
                if (wg == tile) {
#pragma unroll
                    for (int of = 4; of <= 16; of <<= 1) {
#pragma unroll
                        for (int k = 0; k < 8; k++) lsum[k] += __shfl_xor_sync(~0u, lsum[k], of);
                    }
                    if (g == 0) {
#pragma unroll
                        for (int jb = 0; jb < 4; jb++)
                            asm volatile("st.shared.v2.f32 [%0], {%1,%2};" ::"r"(LRED + (warp * 32 + 8 * jb + 2 * q) * 4), "f"(lsum[2 * jb]), "f"(lsum[2 * jb + 1]) : "memory");
                    }
                    if (tile == 1) {
                        asm volatile("bar.sync 3, 128;" ::: "memory");
                        if (wq == 0) {
                            float l0 = 0.f, l1 = 0.f;
#pragma unroll
                            for (int w = 0; w < 4; w++) { l0 += ldsf(LRED + (w * 32 + lane) * 4); l1 += ldsf(LRED + ((w + 4) * 32 + lane) * 4); }
                            const float l = l0 * ldsf(ALPHA + lane * 4) + l1;
                            const float mf = ldsf(MRUN + 256 + lane * 4);
                            if ((lane >> 4) == (int)rank) {
                                asm volatile("st.shared.v2.f32 [%0], {%1,%2};" ::"r"(OST + (lane & 15) * 8), "f"(mf), "f"(l) : "memory");
                            } else {
                                mbar_wait(BAR(B_PEER0));
                                st_async2(mapa(PST + (lane & 15) * 8, rank ^ 1), mf, l, mapa(BAR(B_XST), rank ^ 1));
                            }
                            __syncwarp();
                            if (lane == 0) mbar_arrive(BAR(B_XST));
                        }
                    }
                }
                if (tile == 0 && wg == 0) {
                    wg_wait0();
                    __syncwarp();
                    if (lane == 0) {
                        mbar_arrive(BAR(B_KV0FREE));
                        asm volatile("mbarrier.arrive.relaxed.cluster.shared::cluster.b64 _, [%0];" ::"r"(mapa(BAR(B_PEER0), rank ^ 1)) : "memory");
                    }
                    TS0(9);
                }
            }
            mbar_wait(BAR(B_PEER0));
            {
                const uint32_t rx = mapa(sb + OFF_XCH + t * 16, rank ^ 1), rb = mapa(BAR(B_XCH), rank ^ 1);
                asm volatile("wgmma.wait_group.sync.aligned 3;" ::: "memory");
                reg_fence(o[0]);
                st_async4(rx, pack_bf16(o[0][8], o[0][9]), pack_bf16(o[0][10], o[0][11]), pack_bf16(o[0][12], o[0][13]), pack_bf16(o[0][14], o[0][15]), rb);
                asm volatile("wgmma.wait_group.sync.aligned 2;" ::: "memory");
                reg_fence(o[1]);
                st_async4(rx + 4096, pack_bf16(o[1][8], o[1][9]), pack_bf16(o[1][10], o[1][11]), pack_bf16(o[1][12], o[1][13]), pack_bf16(o[1][14], o[1][15]), rb);
                asm volatile("wgmma.wait_group.sync.aligned 1;" ::: "memory");
                reg_fence(o[2]);
                st_async4(rx + 8192, pack_bf16(o[2][8], o[2][9]), pack_bf16(o[2][10], o[2][11]), pack_bf16(o[2][12], o[2][13]), pack_bf16(o[2][14], o[2][15]), rb);
                wg_wait0();
                reg_fence(o[3]);
                st_async4(rx + 12288, pack_bf16(o[3][8], o[3][9]), pack_bf16(o[3][10], o[3][11]), pack_bf16(o[3][12], o[3][13]), pack_bf16(o[3][14], o[3][15]), rb);
            }
            TS0(11);
            mbar_wait(BAR(B_XST));
            float ca[4], cb[4];
#pragma unroll
            for (int k = 0; k < 4; k++) {
                const int n = 8 * (k >> 1) + 2 * q + (k & 1);
                const float2 so = ldsf2(OST + n * 8), sp = ldsf2(PST + n * 8);
                const float mx = fmaxf(so.x, sp.x);
                ca[k] = ex2(so.x - mx);
                cb[k] = ex2(sp.x - mx);
            }
#pragma unroll
            for (int mt = 0; mt < 4; mt++) {
                o[mt][0] *= ca[0]; o[mt][1] *= ca[1]; o[mt][2] *= ca[0]; o[mt][3] *= ca[1];
                o[mt][4] *= ca[2]; o[mt][5] *= ca[3]; o[mt][6] *= ca[2]; o[mt][7] *= ca[3];
            }
            if (warp == 0) {
                const float2 so = ldsf2(OST + (lane & 15) * 8), sp = ldsf2(PST + (lane & 15) * 8);
                const float mx = fmaxf(so.x, sp.x);
                const float l = so.y * ex2(so.x - mx) + sp.y * ex2(sp.x - mx);
                const float ln = __shfl_down_sync(~0u, l, 1), mn = __shfl_down_sync(~0u, mx, 1);
                if (lane < 16 && (lane & 1) == 0) put4(&g_stat[((rank * 4 + (lane >> 2)) * 64 + (i >> 1)) * 2 + ((lane >> 1) & 1)], mx, l, mn, ln, tag);
            }
            const uint32_t keep = (g == 0) ? 0xFFFEFFFEu : 0xFFFFFFFFu;
            const uint32_t tg = (g == 0) ? ((ep & 1u) ? 0u : 0x00010001u) : 0u;
            const int hl = lane & 15, mi2 = lane >> 4;
            mbar_wait(BAR(B_XCH));
            TS0(46);
#pragma unroll
            for (int mt = 0; mt < 4; mt++) {
                const uint4 r = lds128(sb + OFF_XCH + mt * 4096 + t * 16);
                const uint32_t lo0 = (pack_bf16(o[mt][0] + cb[0] * bf_lo(r.x), o[mt][1] + cb[1] * bf_hi(r.x)) & keep) | tg;
                const uint32_t hi0 = (pack_bf16(o[mt][2] + cb[0] * bf_lo(r.y), o[mt][3] + cb[1] * bf_hi(r.y)) & keep) | tg;
                const uint32_t lo1 = (pack_bf16(o[mt][4] + cb[2] * bf_lo(r.z), o[mt][5] + cb[3] * bf_hi(r.z)) & keep) | tg;
                const uint32_t hi1 = (pack_bf16(o[mt][6] + cb[2] * bf_lo(r.w), o[mt][7] + cb[3] * bf_hi(r.w)) & keep) | tg;
                const uint32_t row = sb + OFF_STG + (wg * 2 + (mt >> 1)) * 4096 + hl * 256;
                const int ch = (mt & 1) * 8 + wq * 2 + mi2;
                stsm4t(row + ((ch ^ (hl & 7)) << 4), lo0, lo1, hi0, hi1);
            }
            fence_async_smem();
            if (wg == 0) asm volatile("bar.sync 2, 128;" ::: "memory"); else asm volatile("bar.sync 3, 128;" ::: "memory");
            if (warp == 4) TS(47);
            if (wq == 0 && lane == 0) {
                bulk_s2g(&g_part[i * 1024 + wg * 512], sb + OFF_STG + wg * 8192, 8192);
                asm volatile("cp.async.bulk.commit_group;" ::: "memory");
                asm volatile("cp.async.bulk.wait_group 0;" ::: "memory");
                if (atomicAdd(reinterpret_cast<unsigned int*>(smem + OFF_MISC + 236), 1u) == 1u) red_cnt(&g_sync[bb * 32 + 1]);
            }
            TS0(12);
        }
        mbar_wait(BAR(B_CLR2));
        TS0(15);
        const uint32_t SCR = sb + OFF_SCR;
        {
            const int b = warp >> 1;
            const uint32_t ptag = par;
            const int pi = lane >> 3, v = (warp & 1) * 8 + (lane & 7);
            const uint4* sp = &g_stat[((hh >> 2) * 64 + b * 16 + (lane & 15)) * 2 + ((hh >> 1) & 1)];
            const uint4* src = &g_part[(2 * (b * 16 + pi) + (hh >> 4)) * 1024 + (jj * 16 + (hh & 15)) * 16 + v];
            float acc[8];
            int it = 0;
            bool ok;
            TS0(62);
            if (warp != 0) mbar_wait_n(BAR(B_WUV), 4);
            if (warp == 0) {
                const unsigned int target = (ep + 1u) * 32u;
                {
                    const unsigned int t_poll = lds32(MISC + 232) + GATE_NS;
#pragma unroll 1
                    while ((int)(gtimer_lo() - t_poll) < 0 && ++it < SPIN_LIMIT) {}
                    it = 0;
                }
                TS(60);
#pragma unroll 1
                while (!__all_sync(~0u, (int)(ld_cnt(&g_sync[(lane & 3) * 32 + 1]) - target) >= 0) && ++it < SPIN_LIMIT) { spin(POLLGAP); }
                TS(63);
                it = 0;
                if (lane == 0) mbar_arrive(BAR(B_G4));
            }
            bar_main();
            gemv_y_load(afr);
            TS0(13);
#pragma unroll 1
            do {
                const uint4 su = ld128(sp);
                uint4 r[4];
#pragma unroll
                for (int k = 0; k < 4; k++) r[k] = ld128(src + (size_t)k * 8 * 1024);
                ok = (su.x & 3u) == tag;
                const float mi = (hh & 1) ? __uint_as_float(su.z) : __uint_as_float(su.x & ~3u), li = (hh & 1) ? __uint_as_float(su.w) : __uint_as_float(su.y);
                float mx = mi;
#pragma unroll
                for (int of = 8; of; of >>= 1) mx = fmaxf(mx, __shfl_xor_sync(~0u, mx, of));
                float wi = ex2(mi - mx);
                float L = wi * li;
#pragma unroll
                for (int of = 8; of; of >>= 1) L += __shfl_xor_sync(~0u, L, of);
                wi = __fdividef(wi, L);
#pragma unroll
                for (int k = 0; k < 8; k++) acc[k] = 0.f;
#pragma unroll
                for (int k = 0; k < 4; k++) {
                    const float w = __shfl_sync(~0u, wi, 4 * k + pi);
                    ok = ok & ((r[k].x & 1u) == ptag);
                    acc[0] += w * bf_lo(r[k].x); acc[1] += w * bf_hi(r[k].x);
                    acc[2] += w * bf_lo(r[k].y); acc[3] += w * bf_hi(r[k].y);
                    acc[4] += w * bf_lo(r[k].z); acc[5] += w * bf_hi(r[k].z);
                    acc[6] += w * bf_lo(r[k].w); acc[7] += w * bf_hi(r[k].w);
                }
            } while (!__all_sync(~0u, ok) && ++it < SPIN_LIMIT);
            {
                const bool u4 = lane & 16, u3 = lane & 8;
                float h4[4], h2[2];
#pragma unroll
                for (int k = 0; k < 4; k++) h4[k] = (u4 ? acc[k + 4] : acc[k]) + __shfl_xor_sync(~0u, u4 ? acc[k] : acc[k + 4], 16);
#pragma unroll
                for (int k = 0; k < 2; k++) h2[k] = (u3 ? h4[k + 2] : h4[k]) + __shfl_xor_sync(~0u, u3 ? h4[k] : h4[k + 2], 8);
                const int ch = v ^ (hh & 7);
                sts32(ACT + b * 272 + (ch * 8 + (u4 ? 4 : 0) + (u3 ? 2 : 0)) * 2, pack_bf16(h2[0], h2[1]));
            }
            bar_main();
            TS0(14);
        }
        gemv_y_put(afr, &g_C[i * 128], ACT, tag);
        TS0(17);
        mbar_wait_n(BAR(B_WO), 4);
        {
            const int blk = lane >> 3, r8 = lane & 7;
            const uint32_t wb = sb + OFF_X + warp * 4096 + ((blk >> 1) * 8 + r8) * 128;
#pragma unroll
            for (int mt = 0; mt < 4; mt++) {
                const uint32_t co = ((2 * mt + (blk & 1)) ^ r8) << 4;
                ldsm4t(afr[2 * mt], wb + co);
                ldsm4t(afr[2 * mt + 1], wb + 16 * 128 + co);
            }
        }
        if (warp == 0) {
            const float4 a = get4sum4(&g_C[hh * 4 * 128 + jj * 32 + lane], 128, tag);
            sts_frag(ACTB, 80, (t >> 4) * 16 + vrr, vb0, a.x, a.y, a.z, a.w);
        }
        bar_main();
        TS0(16);
        {
            uint32_t b[4];
            ldsm4(b, ACTB + (lane & 3) * 80 + (lane >> 3) * 16);
            uint32_t px[4], py[4];
#pragma unroll
            for (int mt = 0; mt < 4; mt++) {
                float d[4] = {0.f, 0.f, 0.f, 0.f};
                mma16816(d, afr[2 * mt], b[0], b[1]);
                mma16816(d, afr[2 * mt + 1], b[2], b[3]);
                px[mt] = (pack_bf16(d[0], d[1]) & ~1u) | par;
                py[mt] = pack_bf16(d[2], d[3]);
            }
            if (q < 2) {
                uint2* dst = &g_O[i * 512 + warp * 64 + g * 2 + q];
#pragma unroll
                for (int mt = 0; mt < 4; mt++) st64(dst + mt * 16, px[mt], py[mt]);
            }
            TS0(18);
        }
        const int V = i * 4 + (t & 3);
        const int vm = (V >> 4) * 16 + ((V & 15) >> 1), vb = (V & 1) * 2;
        float4 x1 = make_float4(0.f, 0.f, 0.f, 0.f);
        {
            mbar_wait(BAR(B_MODV));
            const float4 r = reduce16(g_O, 128, par, G6ADELAY);
            if (t < 4) {
                const float4 x0 = ldsf4(MISC + 32 + t * 16), ga = ldsf4(MISC + 96 + t * 16);
                x1 = make_float4(x0.x + ga.x * r.x, x0.y + ga.y * r.y, x0.z + ga.z * r.z, x0.w + ga.w * r.w);
                put2(&g_X1[i * 16 + t], x1.x, x1.y, x1.z, x1.w, par);
            }
            TS0(19);
        }
        if (i < NFFN) {
            float4 mv[4];
#pragma unroll
            for (int k = 0; k < 4; k++) {
                uint4 u = lds128(sb + OFF_SBCB + (t + 256 * k) * 16);
                int it = 0;
                while ((u.x & 3u) != tag && ++it < SPIN_LIMIT) u = ld128(&g_M[512 + t + 256 * k]);
                mv[k] = as_f4(u);
            }
            mbar_wait_n(BAR(B_W1), 4);
            {
                const int blk = lane >> 3, r8 = lane & 7;
                const uint32_t w1r = sb + OFF_Z + (warp * 64 + (blk >> 1) * 8 + r8) * 32 + (((blk & 1) ^ ((r8 >> 2) & 1)) << 4);
                const uint32_t w2r = sb + OFF_W2 + warp * 2048 + ((blk >> 1) * 8 + r8) * 128;
#pragma unroll
                for (int k = 0; k < 4; k++) {
                    ldsm4t(afr[k], w1r + k * 512);
                    ldsm4t(afr[4 + k], w2r + (((2 * k + (blk & 1)) ^ r8) << 4));
                }
            }
            TS0(21);
            uint2 ua, ub;
            {
                int it = 0;
#pragma unroll 1
                do { ua = ld64(&g_X1[(t >> 2) * 16 + (t & 3)]); ub = ld64(&g_X1[(t >> 2) * 16 + (t & 3) + 1024]); } while (!__all_sync(~0u, (((ua.x ^ par) | (ub.x ^ par)) & 1u) == 0) && ++it < SPIN_LIMIT);
            }
            const float4 a = as_f4(ua), b = as_f4(ub);
            float s0 = (a.x + a.z) + (b.x + b.z), s1 = (a.y + a.w) + (b.y + b.w);
            float q0 = (a.x * a.x + a.z * a.z) + (b.x * b.x + b.z * b.z), q1 = (a.y * a.y + a.w * a.w) + (b.y * b.y + b.w * b.w);
#pragma unroll
            for (int of = 2; of <= 16; of <<= 1) {
                s0 += __shfl_xor_sync(~0u, s0, of); s1 += __shfl_xor_sync(~0u, s1, of);
                q0 += __shfl_xor_sync(~0u, q0, of); q1 += __shfl_xor_sync(~0u, q1, of);
            }
            const uint32_t ST = SCR + 1024, ACT2 = SCR + 4096;
            if (lane < 2) stsf4(ST + (warp * 2 + lane) * 16, make_float4(s0, q0, s1, q1));
            bar_main();
            TS0(20);
            float4 tot = make_float4(0.f, 0.f, 0.f, 0.f);
#pragma unroll
            for (int w = 0; w < 8; w++) add4(tot, ldsf4(ST + (w * 2 + (t & 1)) * 16));
            const float mean0 = tot.x * (1.f / 512.f), mean1 = tot.z * (1.f / 512.f);
            const float r0 = rsqrtf(fmaxf(tot.y * (1.f / 512.f) - mean0 * mean0, 0.f) + 1e-5f);
            const float r1 = rsqrtf(fmaxf(tot.w * (1.f / 512.f) - mean1 * mean1, 0.f) + 1e-5f);
            const int m0 = (t >> 4) * 16 + vrr;
            sts_frag(ACT2, 1040, m0, vb0, (a.x - mean0) * r0 * (1.f + mv[2].x) + mv[0].x, (a.y - mean1) * r1 * (1.f + mv[2].y) + mv[0].y,
                     (a.z - mean0) * r0 * (1.f + mv[2].z) + mv[0].z, (a.w - mean1) * r1 * (1.f + mv[2].w) + mv[0].w);
            sts_frag(ACT2, 1040, m0 + 256, vb0, (b.x - mean0) * r0 * (1.f + mv[3].x) + mv[1].x, (b.y - mean1) * r1 * (1.f + mv[3].y) + mv[1].y,
                     (b.z - mean0) * r0 * (1.f + mv[3].z) + mv[1].z, (b.w - mean1) * r1 * (1.f + mv[3].w) + mv[1].w);
            bar_main();
            float d[4] = {0.f, 0.f, 0.f, 0.f};
            {
                const uint32_t brow = ACT2 + (lane & 3) * 1040 + (warp * 64 + (lane >> 3) * 8) * 2;
                uint32_t b0[4], b1[4];
                ldsm4(b0, brow);
                ldsm4(b1, brow + 64);
                float e[4] = {0.f, 0.f, 0.f, 0.f};
                mma16816(d, afr[0], b0[0], b0[1]);
                mma16816(e, afr[1], b0[2], b0[3]);
                mma16816(d, afr[2], b1[0], b1[1]);
                mma16816(e, afr[3], b1[2], b1[3]);
                d[0] += e[0]; d[1] += e[1]; d[2] += e[2]; d[3] += e[3];
            }
            const uint32_t HR = SCR + 2048;
            if (q < 2) {
                const uint32_t a0 = HR + (warp * 64 + (2 * q) * 16 + g) * 4;
                stsf(a0, d[0]); stsf(a0 + 64, d[1]); stsf(a0 + 32, d[2]); stsf(a0 + 96, d[3]);
            }
            bar_main();
            float2 h0 = make_float2(0.f, 0.f), h1 = h0;
#pragma unroll
            for (int w = 0; w < 8; w++) {
                const float2 u = ldsf2(HR + (w * 64 + (g & 3) * 16 + 2 * q) * 4), v = ldsf2(HR + (w * 64 + (g & 3) * 16 + 2 * q + 8) * 4);
                h0.x += u.x; h0.y += u.y; h1.x += v.x; h1.y += v.y;
            }
            const uint32_t b0r = pack_bf16(fmaxf(h0.x, 0.f), fmaxf(h0.y, 0.f)), b1r = pack_bf16(fmaxf(h1.x, 0.f), fmaxf(h1.y, 0.f));
            TS0(22);
            uint32_t px[4], py[4];
#pragma unroll
            for (int mt = 0; mt < 4; mt++) {
                float e[4] = {0.f, 0.f, 0.f, 0.f};
                mma16816(e, afr[4 + mt], b0r, b1r);
                px[mt] = (pack_bf16(e[0], e[1]) & ~1u) | par;
                py[mt] = pack_bf16(e[2], e[3]);
            }
            if (q < 2) {
                uint2* dst = &g_F[i * 512 + warp * 64 + g * 2 + q];
#pragma unroll
                for (int mt = 0; mt < 4; mt++) st64(dst + mt * 16, px[mt], py[mt]);
            }
            TS0(23);
        }
        {
            const float4 r = reduce16(g_F, NFFN, par, i < NFFN ? HOPDELAY : FFNDELAY);
            if (t < 4) {
                const float4 gb = ldsf4(MISC + 96 + 64 + t * 16);
                p.out[vb * 512 + vm] = __float2bfloat16_rn(x1.x + gb.x * r.x);
                p.out[(vb + 1) * 512 + vm] = __float2bfloat16_rn(x1.y + gb.y * r.y);
                p.out[vb * 512 + vm + 8] = __float2bfloat16_rn(x1.z + gb.z * r.z);
                p.out[(vb + 1) * 512 + vm + 8] = __float2bfloat16_rn(x1.w + gb.w * r.w);
            }
            if (i == 0 && t < NSYNC) g_sync[t * 32] = ep + 1u;
            TS0(24);
        }
    }
}

typedef CUresult (*EncodeFn)(CUtensorMap*, CUtensorMapDataType, cuuint32_t, void*, const cuuint64_t*, const cuuint64_t*, const cuuint32_t*,
                             const cuuint32_t*, CUtensorMapInterleave, CUtensorMapSwizzle, CUtensorMapL2promotion, CUtensorMapFloatOOBfill);

void make_map(EncodeFn enc, CUtensorMap* m, const void* base, int rank, const cuuint64_t* dims, const cuuint64_t* strides, const cuuint32_t* box,
              CUtensorMapSwizzle sw) {
    cuuint32_t es[3] = {1, 1, 1};
    CUresult r = enc(m, CU_TENSOR_MAP_DATA_TYPE_BFLOAT16, rank, const_cast<void*>(base), dims, strides, box, es, CU_TENSOR_MAP_INTERLEAVE_NONE, sw,
                     CU_TENSOR_MAP_L2_PROMOTION_NONE, CU_TENSOR_MAP_FLOAT_OOB_FILL_NONE);
    if (r != CUDA_SUCCESS) fprintf(stderr, "cuTensorMapEncodeTiled failed: %d\n", (int)r);
}
void map2d(EncodeFn enc, CUtensorMap* m, const void* base, uint64_t rows, uint64_t cols, uint32_t boxr, uint32_t boxc, CUtensorMapSwizzle sw) {
    cuuint64_t dims[2] = {cols, rows};
    cuuint64_t strides[1] = {cols * 2};
    cuuint32_t box[2] = {boxc, boxr};
    make_map(enc, m, base, 2, dims, strides, box, sw);
}
void map3d(EncodeFn enc, CUtensorMap* m, const void* base, uint64_t rows, uint32_t boxr, uint32_t boxb) {
    cuuint64_t dims[3] = {64, rows, 8};
    cuuint64_t strides[2] = {1024, 128};
    cuuint32_t box[3] = {64, boxr, boxb};
    make_map(enc, m, base, 3, dims, strides, box, CU_TENSOR_MAP_SWIZZLE_128B);
}

}

extern "C" void kernel_launch(void* const* d_in, const int* in_sizes, int n_in, void* d_out, int out_size) {
    (void)in_sizes; (void)n_in; (void)out_size;
    static EncodeFn enc = nullptr;
    static void* qabs_ptr = nullptr;
    if (!enc) {
        void* fn = nullptr;
        cudaDriverEntryPointQueryResult st;
        cudaGetDriverEntryPoint("cuTensorMapEncodeTiled", &fn, cudaEnableDefault, &st);
        enc = (EncodeFn)fn;
        cudaFuncSetAttribute(fused_kernel, cudaFuncAttributeMaxDynamicSharedMemorySize, SMEM_BYTES);
        cudaGetSymbolAddress(&qabs_ptr, g_qabs);
    }
    Params p;
    map2d(enc, &p.kv, d_in[1], 16384, 512, 64, 64, CU_TENSOR_MAP_SWIZZLE_128B);
    map2d(enc, &p.wq, d_in[2], 512, 4096, 64, 64, CU_TENSOR_MAP_SWIZZLE_128B);
    map2d(enc, &p.wuk, d_in[3], 512, 4096, 64, 64, CU_TENSOR_MAP_SWIZZLE_128B);
    map2d(enc, &p.wuv, d_in[4], 512, 4096, 64, 64, CU_TENSOR_MAP_SWIZZLE_128B);
    map3d(enc, &p.wo, d_in[5], 4096, 32, 2);
    map2d(enc, &p.w1, d_in[7], 512, 1376, 256, 16, CU_TENSOR_MAP_SWIZZLE_32B);
    map3d(enc, &p.w2, d_in[8], 1376, 16, 4);
    map2d(enc, &p.wmod, d_in[10], 512, 3072, 256, 16, CU_TENSOR_MAP_SWIZZLE_32B);
    map3d(enc, &p.qabs, qabs_ptr, 128, 32, 4);
    map2d(enc, &p.wmoda, d_in[10], 512, 3072, 128, 16, CU_TENSOR_MAP_SWIZZLE_32B);
    p.x = (const __nv_bfloat16*)d_in[0];
    p.c = (const __nv_bfloat16*)d_in[9];
    p.wmodp = (const __nv_bfloat16*)d_in[10];
    p.out = (__nv_bfloat16*)d_out;
    fused_kernel<<<NCTA, NTHREADS, SMEM_BYTES, cudaStreamPerThread>>>(p);
}
```

```cpp
#include <cuda_runtime.h>
#include <cuda_bf16.h>
#include <cuda.h>
#include <stdint.h>
#include <stdio.h>

namespace {

constexpr int NCTA = 128;
constexpr int NTHREADS = 320;
constexpr int NFFN = 86;
#define WINDOW 5
#define DT_0 550
#define DT_F 345
#define DT_S 330
#define DT_T 320
#define DT_T2 400
#define QK_EARLY 4
#define GATE_NS 3600
#define G6ADELAY 300
#define HOPDELAY 300
#define FFNDELAY 2300

constexpr uint32_t OFF_KV = 0;
constexpr uint32_t OFF_X = 131072;
constexpr uint32_t OFF_Y = 163840;
constexpr uint32_t OFF_Z = 196608;
constexpr uint32_t OFF_P = 212992;
constexpr uint32_t OFF_S = 221184;
constexpr uint32_t OFF_ACT = 225344;
constexpr uint32_t OFF_RED = 227648;
constexpr uint32_t OFF_BAR = 229696;
constexpr uint32_t OFF_MISC = 230208;
constexpr uint32_t SMEM_BYTES = 230720;
constexpr uint32_t OFF_STG = OFF_KV;
constexpr uint32_t OFF_XCH = OFF_KV + 16384;
constexpr uint32_t OFF_W2 = OFF_KV + 32768;
constexpr uint32_t OFF_SBCB = OFF_KV + 49152;
constexpr uint32_t OFF_SCR = OFF_KV + 65536;

enum {
    B_WQ = 0,
    B_WUK = 4,
    B_KV = 8,
    B_MOD = 24,
    B_WUV = 26,
    B_WO = 30,
    B_W1 = 34,
    B_W2 = 36,
    B_QABS = 38,
    B_YFREE = 39,
    B_XFREE = 40,
    B_ZFREE = 41,
    B_KV0FREE = 42,
    B_P3 = 43,
    B_CLR2 = 44,
    B_MODV = 45,
    B_WA = 46,
    B_EP = 47,
    B_PEER0 = 48,
    B_XCH = 49,
    B_G4 = 50,
    B_XST = 51,
    B_COUNT = 52
};

struct alignas(64) Params {
    CUtensorMap kv, wq, wuk, wuv, wo, w1, w2, wmod, qabs, wmoda;
    const __nv_bfloat16* x;
    const __nv_bfloat16* c;
    __nv_bfloat16* out;
};

__device__ __align__(128) uint4 g_H[128 * 32];
__device__ __align__(128) uint4 g_Q[128 * 128];
__device__ __align__(128) __nv_bfloat16 g_qabs[4 * 32 * 512];
__device__ __align__(128) uint4 g_part[128 * 4 * 16 * 16];
__device__ __align__(128) uint4 g_stat[8 * 64 * 2];
__device__ __align__(128) uint4 g_C[128 * 128];
__device__ __align__(128) uint2 g_O[128 * 512];
__device__ __align__(128) uint2 g_X1[128 * 16];
__device__ __align__(128) uint2 g_F[NFFN * 512];
__device__ __align__(128) uint4 g_M[4 * 512];
constexpr int NSYNC = 8;
__device__ __align__(128) unsigned int g_sync[NSYNC * 32];

__device__ __forceinline__ uint32_t smem_u32(const void* p) { return (uint32_t)__cvta_generic_to_shared(p); }
__device__ __forceinline__ void mbar_init(uint32_t bar, int cnt) { asm volatile("mbarrier.init.shared::cta.b64 [%0], %1;" ::"r"(bar), "r"(cnt) : "memory"); }
__device__ __forceinline__ void mbar_expect_tx(uint32_t bar, uint32_t bytes) { asm volatile("mbarrier.arrive.expect_tx.shared::cta.b64 _, [%0], %1;" ::"r"(bar), "r"(bytes) : "memory"); }
__device__ __forceinline__ void mbar_arrive(uint32_t bar) { asm volatile("mbarrier.arrive.shared::cta.b64 _, [%0];" ::"r"(bar) : "memory"); }
constexpr int SPIN_LIMIT = 1 << 20;
__device__ __forceinline__ void mbar_wait(uint32_t bar) {
    asm volatile("{\n.reg .pred p;\n.reg .u32 n;\nmov.u32 n, 0;\n"
                 "LW:\nmbarrier.try_wait.parity.shared::cta.b64 p, [%0], 0;\n@p bra LD;\n"
                 "add.u32 n, n, 1;\nsetp.lt.u32 p, n, 262144;\n@p bra LW;\nLD:\n}" ::"r"(bar) : "memory");
}
__device__ __forceinline__ bool mbar_test(uint32_t bar) {
    uint32_t ok;
    asm volatile("{\n.reg .pred p;\nmbarrier.test_wait.parity.shared::cta.b64 p, [%1], 0;\nselp.u32 %0, 1, 0, p;\n}" : "=r"(ok) : "r"(bar) : "memory");
    return ok;
}
__device__ __forceinline__ void mbar_wait_n(uint32_t bar, int n) {
#pragma unroll 1
    for (int k = 0; k < n; k++) mbar_wait(bar + k * 8);
}
__device__ __forceinline__ void bar_main() { asm volatile("bar.sync 1, 256;" ::: "memory"); }
__device__ __forceinline__ void fence_async_smem() { asm volatile("fence.proxy.async.shared::cta;" ::: "memory"); }

__device__ __forceinline__ uint4 ld128(const uint4* p) {
    uint4 v;
    asm volatile("{\n.reg .b128 t;\n.reg .b64 lo, hi;\nld.relaxed.gpu.global.b128 t, [%4];\nmov.b128 {lo, hi}, t;\nmov.b64 {%0,%1}, lo;\nmov.b64 {%2,%3}, hi;\n}"
                 : "=r"(v.x), "=r"(v.y), "=r"(v.z), "=r"(v.w) : "l"(p) : "memory");
    return v;
}
__device__ __forceinline__ void st128(uint4* p, uint4 v) {
    asm volatile("{\n.reg .b128 t;\n.reg .b64 lo, hi;\nmov.b64 lo, {%1,%2};\nmov.b64 hi, {%3,%4};\nmov.b128 t, {lo, hi};\nst.relaxed.gpu.global.b128 [%0], t;\n}"
                 ::"l"(p), "r"(v.x), "r"(v.y), "r"(v.z), "r"(v.w) : "memory");
}
__device__ __forceinline__ uint4 ldnc128_if(const void* p, bool c) {
    uint4 v;
    asm volatile("{\n.reg .pred p;\nsetp.ne.u32 p, %5, 0;\nmov.u32 %0, 0;\nmov.u32 %1, 0;\nmov.u32 %2, 0;\nmov.u32 %3, 0;\n@p ld.global.nc.v4.u32 {%0,%1,%2,%3}, [%4];\n}"
                 : "=r"(v.x), "=r"(v.y), "=r"(v.z), "=r"(v.w) : "l"(p), "r"((uint32_t)c));
    return v;
}
__device__ __forceinline__ uint32_t ldnc32(const void* p) { uint32_t v; asm volatile("ld.global.nc.u32 %0, [%1];" : "=r"(v) : "l"(p)); return v; }
__device__ __forceinline__ uint32_t ldnc16(const void* p) { uint32_t v; asm volatile("ld.global.nc.u16 %0, [%1];" : "=r"(v) : "l"(p)); return v; }
__device__ __forceinline__ unsigned int ld_epoch(const unsigned int* p) { unsigned int v; asm volatile("ld.relaxed.gpu.global.u32 %0, [%1];" : "=r"(v) : "l"(p)); return v; }
__device__ __forceinline__ void put4(uint4* p, float a, float b, float c, float d, uint32_t tag) {
    st128(p, make_uint4((__float_as_uint(a) & ~3u) | tag, __float_as_uint(b), __float_as_uint(c), __float_as_uint(d)));
}
__device__ __forceinline__ float4 as_f4(uint4 v) {
    return make_float4(__uint_as_float(v.x & ~3u), __uint_as_float(v.y), __uint_as_float(v.z), __uint_as_float(v.w));
}
__device__ __forceinline__ void add4(float4& a, const float4& b) { a.x += b.x; a.y += b.y; a.z += b.z; a.w += b.w; }
__device__ __forceinline__ float4 get4(const uint4* p, bool act, uint32_t tag) {
    uint4 v = make_uint4(tag, 0, 0, 0);
    int it = 0;
#pragma unroll 1
    do { if (act) v = ld128(p); } while (!__all_sync(~0u, (v.x & 3u) == tag) && ++it < SPIN_LIMIT);
    return as_f4(v);
}
__device__ __forceinline__ uint2 ld64(const uint2* p) { uint2 v; asm volatile("{\n.reg .b64 t;\nld.relaxed.gpu.global.b64 t, [%2];\nmov.b64 {%0,%1}, t;\n}" : "=r"(v.x), "=r"(v.y) : "l"(p) : "memory"); return v; }
__device__ __forceinline__ void st64(uint2* p, uint32_t x, uint32_t y) { asm volatile("{\n.reg .b64 t;\nmov.b64 t, {%1,%2};\nst.relaxed.gpu.global.b64 [%0], t;\n}" ::"l"(p), "r"(x), "r"(y) : "memory"); }
__device__ __forceinline__ uint32_t pack_bf16(float lo, float hi);
__device__ __forceinline__ void put2(uint2* p, float a, float b, float c, float d, uint32_t par) { st64(p, (pack_bf16(a, b) & ~1u) | par, pack_bf16(c, d)); }
__device__ __forceinline__ float4 as_f4(uint2 v) {
    return make_float4(__uint_as_float(v.x << 16), __uint_as_float(v.x & 0xffff0000u), __uint_as_float(v.y << 16), __uint_as_float(v.y & 0xffff0000u));
}
__device__ __forceinline__ float4 get4sum4(const uint4* p0, int stride, uint32_t tag) {
    uint4 u0, u1, u2, u3;
    int it = 0;
#pragma unroll 1
    do { u0 = ld128(p0); u1 = ld128(p0 + stride); u2 = ld128(p0 + 2 * stride); u3 = ld128(p0 + 3 * stride); }
    while (!__all_sync(~0u, ((u0.x ^ tag) & 3u) == 0 && ((u1.x ^ tag) & 3u) == 0 && ((u2.x ^ tag) & 3u) == 0 && ((u3.x ^ tag) & 3u) == 0) && ++it < SPIN_LIMIT);
    float4 a = as_f4(u0), b = as_f4(u2);
    add4(a, as_f4(u1));
    add4(b, as_f4(u3));
    add4(a, b);
    return a;
}
__device__ __forceinline__ uint32_t pack_bf16(float lo, float hi) {
    uint32_t r;
    asm("cvt.rn.bf16x2.f32 %0, %1, %2;" : "=r"(r) : "f"(hi), "f"(lo));
    return r;
}
__device__ __forceinline__ float bf_lo(uint32_t u) { return __uint_as_float(u << 16); }
__device__ __forceinline__ float bf_hi(uint32_t u) { return __uint_as_float(u & 0xffff0000u); }
__device__ __forceinline__ float ex2(float x) { float y; asm("ex2.approx.ftz.f32 %0, %1;" : "=f"(y) : "f"(x)); return y; }

__device__ __forceinline__ void ldsm4(uint32_t (&r)[4], uint32_t addr) {
    asm volatile("ldmatrix.sync.aligned.m8n8.x4.shared.b16 {%0,%1,%2,%3}, [%4];" : "=r"(r[0]), "=r"(r[1]), "=r"(r[2]), "=r"(r[3]) : "r"(addr) : "memory");
}
__device__ __forceinline__ void ldsm4t(uint32_t (&r)[4], uint32_t addr) {
    asm volatile("ldmatrix.sync.aligned.m8n8.x4.trans.shared.b16 {%0,%1,%2,%3}, [%4];" : "=r"(r[0]), "=r"(r[1]), "=r"(r[2]), "=r"(r[3]) : "r"(addr) : "memory");
}
__device__ __forceinline__ void stsm4t(uint32_t addr, uint32_t r0, uint32_t r1, uint32_t r2, uint32_t r3) {
    asm volatile("stmatrix.sync.aligned.m8n8.x4.trans.shared.b16 [%0], {%1,%2,%3,%4};" ::"r"(addr), "r"(r0), "r"(r1), "r"(r2), "r"(r3) : "memory");
}
__device__ __forceinline__ void mma16816(float (&d)[4], const uint32_t (&a)[4], uint32_t b0, uint32_t b1) {
    asm volatile("mma.sync.aligned.m16n8k16.row.col.f32.bf16.bf16.f32 {%0,%1,%2,%3}, {%4,%5,%6,%7}, {%8,%9}, {%0,%1,%2,%3};"
                 : "+f"(d[0]), "+f"(d[1]), "+f"(d[2]), "+f"(d[3]) : "r"(a[0]), "r"(a[1]), "r"(a[2]), "r"(a[3]), "r"(b0), "r"(b1));
}
__device__ __forceinline__ void sts32(uint32_t a, uint32_t v) { asm volatile("st.shared.b32 [%0], %1;" ::"r"(a), "r"(v) : "memory"); }
__device__ __forceinline__ void sts16(uint32_t a, float v) {
    __nv_bfloat16 h = __float2bfloat16_rn(v);
    asm volatile("st.shared.b16 [%0], %1;" ::"r"(a), "h"(*reinterpret_cast<unsigned short*>(&h)) : "memory");
}
__device__ __forceinline__ void stsf(uint32_t a, float v) { asm volatile("st.shared.f32 [%0], %1;" ::"r"(a), "f"(v) : "memory"); }
__device__ __forceinline__ void stsf4(uint32_t a, float4 v) { asm volatile("st.shared.v4.f32 [%0], {%1,%2,%3,%4};" ::"r"(a), "f"(v.x), "f"(v.y), "f"(v.z), "f"(v.w) : "memory"); }
__device__ __forceinline__ uint32_t lds32(uint32_t a) { uint32_t v; asm volatile("ld.shared.b32 %0, [%1];" : "=r"(v) : "r"(a) : "memory"); return v; }
__device__ __forceinline__ float ldsf(uint32_t a) { float v; asm volatile("ld.shared.f32 %0, [%1];" : "=f"(v) : "r"(a) : "memory"); return v; }
__device__ __forceinline__ float2 ldsf2(uint32_t a) { float2 v; asm volatile("ld.shared.v2.f32 {%0,%1}, [%2];" : "=f"(v.x), "=f"(v.y) : "r"(a) : "memory"); return v; }
__device__ __forceinline__ float4 ldsf4(uint32_t a) { float4 v; asm volatile("ld.shared.v4.f32 {%0,%1,%2,%3}, [%4];" : "=f"(v.x), "=f"(v.y), "=f"(v.z), "=f"(v.w) : "r"(a) : "memory"); return v; }
__device__ __forceinline__ uint4 lds128(uint32_t a) { uint4 v; asm volatile("ld.shared.v4.b32 {%0,%1,%2,%3}, [%4];" : "=r"(v.x), "=r"(v.y), "=r"(v.z), "=r"(v.w) : "r"(a) : "memory"); return v; }

__device__ __forceinline__ void tma2d(uint32_t dst, const CUtensorMap* m, int c0, int c1, uint32_t bar, uint32_t bytes, uint64_t pol) {
    asm volatile("{\n.reg .pred p;\nelect.sync _|p, 0xffffffff;\n"
                 "@p mbarrier.arrive.expect_tx.shared::cta.b64 _, [%2], %6;\n"
                 "@p cp.async.bulk.tensor.2d.shared::cluster.global.mbarrier::complete_tx::bytes.L2::cache_hint [%0], [%1, {%3, %4}], [%2], %5;\n}"
                 ::"r"(dst), "l"(m), "r"(bar), "r"(c0), "r"(c1), "l"(pol), "r"(bytes) : "memory");
}
__device__ __forceinline__ void tma3d(uint32_t dst, const CUtensorMap* m, int c0, int c1, int c2, uint32_t bar, uint32_t bytes, uint64_t pol) {
    asm volatile("{\n.reg .pred p;\nelect.sync _|p, 0xffffffff;\n"
                 "@p mbarrier.arrive.expect_tx.shared::cta.b64 _, [%2], %7;\n"
                 "@p cp.async.bulk.tensor.3d.shared::cluster.global.mbarrier::complete_tx::bytes.L2::cache_hint [%0], [%1, {%3, %4, %5}], [%2], %6;\n}"
                 ::"r"(dst), "l"(m), "r"(bar), "r"(c0), "r"(c1), "r"(c2), "l"(pol), "r"(bytes) : "memory");
}
__device__ __forceinline__ void tma2d_na(uint32_t dst, const CUtensorMap* m, int c0, int c1, uint32_t bar, uint64_t pol) {
    asm volatile("{\n.reg .pred p;\nelect.sync _|p, 0xffffffff;\n"
                 "@p cp.async.bulk.tensor.2d.shared::cluster.global.mbarrier::complete_tx::bytes.L2::cache_hint [%0], [%1, {%3, %4}], [%2], %5;\n}"
                 ::"r"(dst), "l"(m), "r"(bar), "r"(c0), "r"(c1), "l"(pol) : "memory");
}
__device__ __forceinline__ uint32_t mapa(uint32_t addr, uint32_t rank) {
    uint32_t r;
    asm("mapa.shared::cluster.u32 %0, %1, %2;" : "=r"(r) : "r"(addr), "r"(rank));
    return r;
}
__device__ __forceinline__ void st_async4(uint32_t raddr, uint32_t a, uint32_t b, uint32_t c, uint32_t d, uint32_t rbar) {
    asm volatile("st.async.weak.shared::cluster.mbarrier::complete_tx::bytes.v4.b32 [%0], {%1,%2,%3,%4}, [%5];" ::"r"(raddr), "r"(a), "r"(b), "r"(c), "r"(d), "r"(rbar) : "memory");
}
__device__ __forceinline__ void st_async2(uint32_t raddr, float a, float b, uint32_t rbar) {
    asm volatile("st.async.weak.shared::cluster.mbarrier::complete_tx::bytes.v2.f32 [%0], {%1,%2}, [%3];" ::"r"(raddr), "f"(a), "f"(b), "r"(rbar) : "memory");
}
__device__ __forceinline__ void tma3d_mc(uint32_t dst, const CUtensorMap* m, int c0, int c1, int c2, uint32_t bar, uint32_t bytes) {
    asm volatile("{\n.reg .pred p;\nelect.sync _|p, 0xffffffff;\n"
                 "@p mbarrier.arrive.expect_tx.shared::cta.b64 _, [%2], %6;\n"
                 "@p cp.async.bulk.tensor.3d.shared::cluster.global.mbarrier::complete_tx::bytes.multicast::cluster [%0], [%1, {%3, %4, %5}], [%2], %7;\n}"
                 ::"r"(dst), "l"(m), "r"(bar), "r"(c0), "r"(c1), "r"(c2), "r"(bytes), "h"((unsigned short)3) : "memory");
}
__device__ __forceinline__ void bulk_s2g(void* dst, uint32_t src, uint32_t bytes) {
    asm volatile("cp.async.bulk.global.shared::cta.bulk_group [%0], [%1], %2;" ::"l"(dst), "r"(src), "r"(bytes) : "memory");
}
__device__ __forceinline__ void prefetch_map(const CUtensorMap* m) { asm volatile("prefetch.tensormap [%0];" ::"l"(m) : "memory"); }

constexpr uint32_t DESC_HI = 64u | (1u << 30);
__device__ __forceinline__ constexpr uint32_t desc_lo(uint32_t addr) { return ((addr & 0x3FFFF) >> 4) | (1u << 16); }
__device__ __forceinline__ void wg_fence() { asm volatile("wgmma.fence.sync.aligned;" ::: "memory"); }
__device__ __forceinline__ void wg_commit() { asm volatile("wgmma.commit_group.sync.aligned;" ::: "memory"); }
__device__ __forceinline__ void wg_wait0() { asm volatile("wgmma.wait_group.sync.aligned 0;" ::: "memory"); }
template <int TA>
__device__ __forceinline__ void wgmma_n32(float (&d)[16], uint32_t alo, uint32_t blo, int scale_d) {
    asm volatile("{\n.reg .pred p;\n.reg .b64 da, db;\nsetp.ne.b32 p, %18, 0;\nmov.b64 da, {%16, %20};\nmov.b64 db, {%17, %20};\n"
                 "wgmma.mma_async.sync.aligned.m64n32k16.f32.bf16.bf16 "
                 "{%0,%1,%2,%3,%4,%5,%6,%7,%8,%9,%10,%11,%12,%13,%14,%15}, da, db, p, 1, 1, %19, 0;\n}"
                 : "+f"(d[0]), "+f"(d[1]), "+f"(d[2]), "+f"(d[3]), "+f"(d[4]), "+f"(d[5]), "+f"(d[6]), "+f"(d[7]),
                   "+f"(d[8]), "+f"(d[9]), "+f"(d[10]), "+f"(d[11]), "+f"(d[12]), "+f"(d[13]), "+f"(d[14]), "+f"(d[15])
                 : "r"(alo), "r"(blo), "r"(scale_d), "n"(TA), "n"(DESC_HI));
}
template <int N>
__device__ __forceinline__ void reg_fence(float (&d)[N]) {
#pragma unroll
    for (int i = 0; i < N; i++) asm volatile("" : "+f"(d[i])::"memory");
}

#define TS(slot)
#define TS0(slot)

__device__ __forceinline__ unsigned int gtimer_lo() {
    unsigned long long t;
    asm volatile("mov.u64 %0, %globaltimer;" : "=l"(t));
    return (unsigned int)t;
}
__device__ __forceinline__ unsigned int clock32() { unsigned int c; asm volatile("mov.u32 %0, %clock;" : "=r"(c)); return c; }
__device__ __forceinline__ void spin(int cycles) {
    if (cycles <= 0) return;
    const unsigned int t0 = clock32();
#pragma unroll 1
    while (clock32() - t0 < (unsigned int)cycles) {}
}
__device__ __forceinline__ unsigned int ld_cnt(const unsigned int* p) {
    unsigned int v;
    asm volatile("ld.relaxed.gpu.global.u32 %0, [%1];" : "=r"(v) : "l"(p) : "memory");
    return v;
}
__device__ __forceinline__ void wait_cnt(const unsigned int* p, unsigned int target) {
    int it = 0;
#pragma unroll 1
    while ((int)(ld_cnt(p) - target) < 0) { if (++it > SPIN_LIMIT) break; }
}
__device__ __forceinline__ void red_cnt(unsigned int* p) { asm volatile("red.relaxed.gpu.global.add.u32 [%0], 1;" ::"l"(p) : "memory"); }

constexpr uint32_t SB0 = 1024;
__device__ __forceinline__ uint32_t smem_base() {
    extern __shared__ __align__(1024) uint8_t smem_dyn[];
    return smem_u32(smem_dyn);
}

__device__ __forceinline__ void gemv_y_load(uint32_t (&a)[8][4]) {
    const int lane = threadIdx.x & 31, warp = threadIdx.x >> 5;
    const int blk = lane >> 3, r8 = lane & 7;
    const int ch = (warp & 3) * 2 + (blk & 1);
    const uint32_t arow = smem_base() + OFF_Y + (warp >> 2) * 16384 + ((blk >> 1) * 8 + r8) * 128 + ((ch ^ r8) << 4);
#pragma unroll
    for (int k = 0; k < 8; k++) ldsm4t(a[k], arow + k * 16 * 128);
}
__device__ __forceinline__ void gemv_y_put(const uint32_t (&a)[8][4], uint4* dst, uint32_t act, uint32_t tag) {
    const int lane = threadIdx.x & 31, warp = threadIdx.x >> 5;
    const uint32_t brow = act + (lane & 3) * 272 + (lane >> 3) * 16;
    uint32_t b[4][4];
#pragma unroll
    for (int k = 0; k < 4; k++) ldsm4(b[k], brow + k * 64);
    float d[4] = {0.f, 0.f, 0.f, 0.f}, e[4] = {0.f, 0.f, 0.f, 0.f};
#pragma unroll
    for (int k = 0; k < 4; k++) {
        mma16816(d, a[2 * k], b[k][0], b[k][1]);
        mma16816(e, a[2 * k + 1], b[k][2], b[k][3]);
    }
    const uint32_t x = (__float_as_uint(d[0] + e[0]) & ~3u) | tag;
    const float y = d[1] + e[1], z = d[2] + e[2], w = d[3] + e[3];
    if ((lane & 3) < 2) st128(dst + warp * 16 + (lane >> 2) * 2 + (lane & 3), make_uint4(x, __float_as_uint(y), __float_as_uint(z), __float_as_uint(w)));
}

__device__ __forceinline__ void gemv_512x16(float (&d)[4], uint32_t tile, uint32_t act, int k0, int nk2, int lane) {
    const int blk = lane >> 3, r8 = lane & 7;
    uint32_t arow = tile + (k0 + (blk >> 1) * 8 + r8) * 32 + (((blk & 1) ^ ((r8 >> 2) & 1)) << 4);
    uint32_t brow = act + (r8 & 3) * 1040 + (k0 + blk * 8) * 2;
#pragma unroll 2
    for (int k2 = 0; k2 < nk2; k2++) {
        uint32_t b[4], a0[4], a1[4];
        ldsm4(b, brow);
        ldsm4t(a0, arow);
        ldsm4t(a1, arow + 512);
        mma16816(d, a0, b[0], b[1]);
        mma16816(d, a1, b[2], b[3]);
        brow += 64;
        arow += 1024;
    }
}

__device__ __noinline__ float4 reduce16(const uint2* base, int n, uint32_t par, int delay) {
    const int t = threadIdx.x, lane = t & 31, warp = t >> 5;
    const uint32_t SCR = smem_base() + OFF_SCR;
    const int pp = t >> 2;
    const uint2* p0 = base + (size_t)pp * 512 + blockIdx.x * 4 + (t & 3);
    const bool act1 = pp + 64 < n;
    spin(delay);
    uint2 u, v = make_uint2(par, 0);
    int it = 0;
#pragma unroll 1
    do { u = ld64(p0); if (act1) v = ld64(p0 + 64 * 512); } while (!__all_sync(~0u, (((u.x ^ par) | (v.x ^ par)) & 1u) == 0) && ++it < SPIN_LIMIT);
    float4 a = as_f4(u);
    if (act1) add4(a, as_f4(v));
#pragma unroll
    for (int of = 4; of <= 16; of <<= 1) {
        a.x += __shfl_xor_sync(~0u, a.x, of); a.y += __shfl_xor_sync(~0u, a.y, of);
        a.z += __shfl_xor_sync(~0u, a.z, of); a.w += __shfl_xor_sync(~0u, a.w, of);
    }
    if (lane < 4) stsf4(SCR + (warp * 4 + lane) * 16, a);
    bar_main();
    float4 r = make_float4(0.f, 0.f, 0.f, 0.f);
    if (t < 4) {
#pragma unroll
        for (int w = 0; w < 8; w++) add4(r, ldsf4(SCR + (w * 4 + t) * 16));
    }
    return r;
}
__device__ __forceinline__ void sts_frag(uint32_t base, uint32_t stride, int m, int b0, float x, float y, float z, float w) {
    const uint32_t a = base + b0 * stride + m * 2;
    sts16(a, x); sts16(a + stride, y); sts16(a + 16, z); sts16(a + stride + 16, w);
}

__global__ void __cluster_dims__(2, 1, 1) __launch_bounds__(NTHREADS, 1) fused_kernel(const __grid_constant__ Params p) {
    extern __shared__ __align__(1024) uint8_t smem[];
    const uint32_t sb = smem_base();
    const int t = threadIdx.x, lane = t & 31;
    const int warp = __shfl_sync(0xffffffffu, t >> 5, 0);
    const int i = blockIdx.x;
    const int hh = i >> 2, jj = i & 3;
    const int bb = i >> 5, chunk = i & 31;
    const uint32_t rank = i & 1;
    auto BAR = [&](int k) { return sb + OFF_BAR + k * 8; };
    const uint32_t MISC = sb + OFF_MISC;

    if (warp == 8) {
        if (lane == 0) {
            TS(0);
            prefetch_map(&p.wmoda);
            prefetch_map(&p.wq);
            mbar_init(BAR(B_WA), 1);
            mbar_init(BAR(0), 1);
            asm volatile("fence.mbarrier_init.release.cluster;" ::: "memory");
            fence_async_smem();
            mbar_expect_tx(BAR(B_WA), 8192);
        }
        __syncwarp();
        uint64_t pol;
        asm volatile("createpolicy.fractional.L2::evict_first.b64 %0, 1.0;" : "=l"(pol));
        tma2d_na(sb + OFF_Z, &p.wmoda, 16 * hh, jj * 128, BAR(B_WA), pol);
        tma2d_na(sb + OFF_Z + 4096, &p.wmoda, 512 + 16 * hh, jj * 128, BAR(B_WA), pol);
        tma2d(sb + OFF_Y, &p.wq, hh * 128, jj * 128, BAR(0), 8192, pol);
        unsigned int due = gtimer_lo() + DT_0;
        if (lane == 0) {
            if ((sb & 0xFFFFFFu) != SB0) __trap();
#pragma unroll
            for (int k = 1; k < 4; k++) mbar_init(BAR(k), 1);
            asm volatile("fence.mbarrier_init.release.cluster;" ::: "memory");
            fence_async_smem();
        }
        __syncwarp();
        asm volatile("bar.arrive 4, 320;" ::: "memory");
        auto pace_dt = [&](int it, unsigned int dt) {
            if (it >= WINDOW) mbar_wait(BAR(0) + (it - WINDOW) * 8);
            int spin_it = 0;
#pragma unroll 1
            while ((int)(gtimer_lo() - due) < 0 && ++spin_it < SPIN_LIMIT) {}
            due += dt;
        };
        auto pace = [&](int it) { pace_dt(it, it < B_KV ? DT_F : (it < B_W1 ? DT_T : DT_T2)); };
        auto tile128 = [&](const CUtensorMap* m, int first, uint32_t dst, int k0) {
#pragma unroll 1
            for (int k = k0; k < 4; k++) {
                pace(first + k);
                tma2d(dst + k * 8192, m, hh * 128 + (k >> 1) * 64, jj * 128 + (k & 1) * 64, BAR(0) + (first + k) * 8, 8192, pol);
            }
        };
        tile128(&p.wq, B_WQ, sb + OFF_Y, 1);
        asm volatile("bar.sync 5, 320;" ::: "memory");
        tile128(&p.wuk, B_WUK, sb + OFF_X, 0);
        TS(61);
#pragma unroll 1
        for (int s = 0; s < 16; s++) {
            pace_dt(B_KV + s, mbar_test(BAR(B_QABS)) ? DT_S : DT_F);
            tma2d(sb + OFF_KV + s * 8192, &p.kv, (s & 7) * 64, bb * 4096 + chunk * 128 + (s >> 3) * 64, BAR(B_KV) + s * 8, 8192, pol);
        }
        if (lane == 0) sts32(MISC + 232, due);
        TS(43);
        mbar_wait(BAR(B_YFREE));
#pragma unroll 1
        for (int k = 0; k < 2; k++) {
            pace(B_MOD + k);
            tma2d(sb + OFF_Z + k * 8192, &p.wmod, 1024 + 16 * i, k * 256, BAR(B_MOD) + k * 8, 8192, pol);
        }
        tile128(&p.wuv, B_WUV, sb + OFF_Y, 0);
        mbar_wait(BAR(B_XFREE));
#pragma unroll 1
        for (int k = 0; k < 4; k++) {
            pace(B_WO + k);
            tma3d(sb + OFF_X + k * 8192, &p.wo, 0, hh * 128 + jj * 32, k * 2, BAR(B_WO) + k * 8, 8192, pol);
        }
        if (i < NFFN) {
            mbar_wait(BAR(B_G4));
            due = gtimer_lo();
            mbar_wait(BAR(B_ZFREE));
#pragma unroll 1
            for (int k = 0; k < 2; k++) {
                pace(B_W1 + k);
                tma2d(sb + OFF_Z + k * 8192, &p.w1, 16 * i, k * 256, BAR(B_W1) + k * 8, 8192, pol);
            }
            mbar_wait(BAR(B_KV0FREE));
#pragma unroll 1
            for (int k = 0; k < 2; k++) {
                pace(B_W2 + k);
                tma3d(sb + OFF_W2 + k * 8192, &p.w2, 0, 16 * i, k * 4, BAR(B_W2) + k * 8, 8192, pol);
            }
        }
        TS(40);
    } else if (warp == 9) {
        unsigned int ep = 0;
        if (lane == 0) {
            ep = ld_epoch(&g_sync[(i % NSYNC) * 32]);
            mbar_init(BAR(B_YFREE), 8);
            mbar_init(BAR(B_XFREE), 4);
            mbar_init(BAR(B_KV0FREE), 8);
            mbar_init(BAR(B_EP), 1);
            mbar_init(BAR(B_PEER0), 8);
            mbar_init(BAR(B_XCH), 1);
            mbar_init(BAR(B_G4), 1);
            mbar_init(BAR(B_XST), 2);
            mbar_expect_tx(BAR(B_XCH), 16384);
            mbar_expect_tx(BAR(B_XST), 128);
            asm volatile("fence.mbarrier_init.release.cluster;" ::: "memory");
        }
        __syncwarp();
        asm volatile("bar.arrive 5, 320;" ::: "memory");
        asm volatile("bar.arrive 4, 320;" ::: "memory");
        if (lane < 9) prefetch_map(&p.kv + lane);
        const uint4 z = make_uint4(0, 0, 0, 0);
        st128(&g_H[i * 32 + lane], z);
#pragma unroll
        for (int k = 0; k < 4; k++) st128(&g_Q[i * 128 + k * 32 + lane], z);
        uint32_t xr = 0;
        if (lane < 16) {
            const int V = i * 4 + (lane >> 2), e = lane & 3;
            const int m = (V >> 4) * 16 + ((V & 15) >> 1) + (e >> 1) * 8, b = (V & 1) * 2 + (e & 1);
            xr = ldnc16(p.x + b * 512 + m);
        }
        asm volatile("bar.sync 6, 288;" ::: "memory");
        __syncwarp();
        if (lane == 0) {
            sts32(MISC + 224, ep);
            sts32(MISC + 236, 0);
            mbar_arrive(BAR(B_EP));
        }
        mbar_wait(BAR(B_EP));
        ep = lds32(MISC + 224);
        const uint32_t tag = 1u + 2u * (ep & 1u);
        if (lane < 16) stsf(MISC + 32 + lane * 4, __uint_as_float(xr << 16));
        mbar_wait(BAR(B_P3));
        wait_cnt(&g_sync[(4 + (i & 3)) * 32 + 1], (ep + 1u) * 128u);
        __syncwarp();
        tma3d_mc(sb + OFF_X + rank * 16384, &p.qabs, 0, bb * 32, rank * 4, BAR(B_QABS), 32768);
        TS(41);
#pragma unroll 1
        for (int k = 0; k < 4; k++) st128(&g_C[i * 128 + k * 32 + lane], z);
        if (lane < 16) st128(&g_M[i * 16 + lane], z);
        {
            const uint32_t inv = ep & 1u;
            const uint4 zi = make_uint4(inv, 0, inv, 0);
            if (lane < 8) st128(reinterpret_cast<uint4*>(&g_X1[i * 16]) + lane, zi);
#pragma unroll 1
            for (int k = 0; k < 8; k++) {
                st128(reinterpret_cast<uint4*>(&g_O[i * 512]) + k * 32 + lane, zi);
                if (i < NFFN) st128(reinterpret_cast<uint4*>(&g_F[i * 512]) + k * 32 + lane, zi);
                spin(100);
            }
        }
        __syncwarp();
        if (lane == 0) mbar_arrive(BAR(B_CLR2));
        TS(44);
        mbar_wait_n(BAR(B_MOD), 2);
        float d[4] = {0.f, 0.f, 0.f, 0.f};
        gemv_512x16(d, sb + OFF_Z, sb + OFF_S, 0, 16, lane);
        __syncwarp();
        if (lane == 0) mbar_arrive(BAR(B_ZFREE));
        if ((lane & 3) < 2) put4(&g_M[i * 16 + (lane >> 2) * 2 + (lane & 3)], d[0], d[1], d[2], d[3], tag);
        __syncwarp();
        if (lane == 0 && i >= 32 && i < 96) red_cnt(&g_sync[4 * 32 + 2]);
        TS(42);
        {
            const float4 v = get4(&g_M[((lane >> 2) & 1) * 3 * 512 + i * 4 + (lane & 3)], lane < 8, tag);
            if (lane < 8) stsf4(MISC + 96 + lane * 16, v);
        }
        __syncwarp();
        if (lane == 0) {
            if (i < NFFN) {
                wait_cnt(&g_sync[4 * 32 + 2], (ep + 1u) * 64u);
                mbar_wait(BAR(B_KV0FREE));
                asm volatile("fence.proxy.async.global;" ::: "memory");
                mbar_expect_tx(BAR(B_MODV), 16384);
                asm volatile("cp.async.bulk.shared::cluster.global.mbarrier::complete_tx::bytes [%0], [%1], %2, [%3];"
                             ::"r"(sb + OFF_SBCB), "l"(&g_M[512]), "r"(16384), "r"(BAR(B_MODV)) : "memory");
            } else {
                mbar_arrive(BAR(B_MODV));
            }
            TS(45);
        }
    } else {
        const uint32_t ACT = sb + OFF_ACT, ACTB = sb + OFF_ACT + 1152, RED = sb + OFF_RED;
        const int g = lane >> 2, q = lane & 3;
        const int vrr = (lane & 15) >> 1, vb0 = (lane & 1) * 2;
        uint32_t cw[4];
        uint4 xv[2];
        uint32_t xh[4];
        {
            const uint4* xp = reinterpret_cast<const uint4*>(p.x + (warp & 3) * 512 + lane * 16);
            xv[0] = ldnc128_if(xp, warp < 4);
            xv[1] = ldnc128_if(xp + 1, warp < 4);
            const __nv_bfloat16* xq = p.x + vb0 * 512 + jj * 128 + warp * 16 + vrr;
            xh[0] = ldnc16(xq); xh[1] = ldnc16(xq + 512); xh[2] = ldnc16(xq + 8); xh[3] = ldnc16(xq + 520);
        }
#pragma unroll
        for (int b = 0; b < 4; b++) cw[b] = ldnc32(p.c + b * 512 + 2 * t);
        if (lane == 0) {
#pragma unroll
            for (int k = 0; k < 5; k++) {
                int idx = 4 + warp * 5 + k;
                if (idx >= B_YFREE) idx = (idx == 39) ? B_ZFREE : (idx == 40 ? B_P3 : (idx == 41 ? B_CLR2 : B_MODV));
                mbar_init(BAR(0) + idx * 8, 1);
            }
            asm volatile("fence.mbarrier_init.release.cluster;" ::: "memory");
        }
        __syncwarp();
        asm volatile("bar.arrive 5, 320;" ::: "memory");
        asm volatile("bar.arrive 6, 288;" ::: "memory");
        asm volatile("bar.sync 4, 320;" ::: "memory");

#pragma unroll
        for (int b = 0; b < 4; b++) {
            const float c0 = bf_lo(cw[b]), c1 = bf_hi(cw[b]);
            sts32(sb + OFF_S + b * 1040 + t * 4, pack_bf16(__fdividef(c0, 1.f + __expf(-c0)), __fdividef(c1, 1.f + __expf(-c1))));
        }
        if (warp < 4) {
            const uint32_t u[8] = {xv[0].x, xv[0].y, xv[0].z, xv[0].w, xv[1].x, xv[1].y, xv[1].z, xv[1].w};
            float s = 0.f, ss = 0.f;
#pragma unroll
            for (int k = 0; k < 8; k++) s += bf_lo(u[k]) + bf_hi(u[k]);
#pragma unroll
            for (int o = 16; o; o >>= 1) s += __shfl_xor_sync(~0u, s, o);
            const float mean = s * (1.f / 512.f);
#pragma unroll
            for (int k = 0; k < 8; k++) { const float d0 = bf_lo(u[k]) - mean, d1 = bf_hi(u[k]) - mean; ss += d0 * d0 + d1 * d1; }
#pragma unroll
            for (int o = 16; o; o >>= 1) ss += __shfl_xor_sync(~0u, ss, o);
            if (lane == 0) { stsf(MISC + warp * 8, mean); stsf(MISC + warp * 8 + 4, rsqrtf(ss * (1.f / 512.f) + 1e-5f)); }
        }
        bar_main();
        mbar_wait(BAR(B_EP));
        const unsigned int ep = lds32(MISC + 224);
        const uint32_t tag = 1u + 2u * (ep & 1u);
        const uint32_t par = (ep & 1u) ^ 1u;
        if (warp < 2) {
            mbar_wait(BAR(B_WA));
            TS0(26);
            float d[4] = {0.f, 0.f, 0.f, 0.f};
            gemv_512x16(d, sb + OFF_Z + warp * 4096 - jj * 4096, sb + OFF_S, jj * 128, 4, lane);
            if (q < 2) put4(&g_H[i * 32 + warp * 16 + g * 2 + q], d[0], d[1], d[2], d[3], tag);
        }
        TS0(1);
        mbar_wait_n(BAR(B_WQ), 4);
        uint32_t afr[8][4];
        gemv_y_load(afr);
        TS0(3);
        {
            const float4 a = get4sum4(&g_H[(4 * (8 * jj + warp)) * 32 + lane], 32, tag);
            const float cx = __shfl_down_sync(~0u, a.x, 16), cy = __shfl_down_sync(~0u, a.y, 16);
            const float cz = __shfl_down_sync(~0u, a.z, 16), cwv = __shfl_down_sync(~0u, a.w, 16);
            if (lane < 16) {
                const float2 s0 = ldsf2(MISC + vb0 * 8), s1 = ldsf2(MISC + vb0 * 8 + 8);
                sts_frag(ACT, 272, warp * 16 + vrr, vb0,
                         (__uint_as_float(xh[0] << 16) - s0.x) * s0.y * (1.f + cx) + a.x,
                         (__uint_as_float(xh[1] << 16) - s1.x) * s1.y * (1.f + cy) + a.y,
                         (__uint_as_float(xh[2] << 16) - s0.x) * s0.y * (1.f + cz) + a.z,
                         (__uint_as_float(xh[3] << 16) - s1.x) * s1.y * (1.f + cwv) + a.w);
            }
        }
        bar_main();
        TS0(2);
        gemv_y_put(afr, &g_Q[i * 128], ACT, tag);
        __syncwarp();
        if (lane == 0) mbar_arrive(BAR(B_YFREE));
        mbar_wait_n(BAR(B_WUK), 4);
        TS0(5);
        if (warp < 4) {
            const float4 a = get4sum4(&g_Q[hh * 4 * 128 + t], 128, tag);
            sts_frag(ACTB, 272, (t >> 4) * 16 + vrr, vb0, a.x, a.y, a.z, a.w);
        }
        bar_main();
        TS0(4);
        {
            float d[4] = {0.f, 0.f, 0.f, 0.f};
            const int blk = lane >> 3, r8 = lane & 7;
            const uint32_t arow = sb + OFF_X + (warp * 16 + (blk & 1) * 8 + r8) * 128;
            const uint32_t brow = ACTB + (r8 & 3) * 272 + blk * 16;
            uint32_t a[8][4], b[4][4];
#pragma unroll
            for (int k = 0; k < 8; k++) ldsm4(a[k], arow + (k >> 2) * 16384 + ((((k & 3) * 2 + (blk >> 1)) ^ r8) << 4));
#pragma unroll
            for (int k = 0; k < 4; k++) ldsm4(b[k], brow + k * 64);
            float e[4] = {0.f, 0.f, 0.f, 0.f};
#pragma unroll
            for (int k = 0; k < 4; k++) {
                mma16816(d, a[2 * k], b[k][0], b[k][1]);
                mma16816(e, a[2 * k + 1], b[k][2], b[k][3]);
            }
            d[0] += e[0]; d[1] += e[1]; d[2] += e[2]; d[3] += e[3];
            const float sc = 0.08838834764831845f * 1.4426950408889634f;
            if (q < 2) sts_frag(RED, 256, warp * 16 + g, 2 * q, d[0] * sc, d[1] * sc, d[2] * sc, d[3] * sc);
            fence_async_smem();
            bar_main();
            if (t == 0) {
#pragma unroll 1
                for (int b = 0; b < 4; b++) bulk_s2g(&g_qabs[(b * 32 + hh) * 512 + jj * 128], RED + b * 256, 256);
                asm volatile("cp.async.bulk.commit_group;" ::: "memory");
                asm volatile("cp.async.bulk.wait_group 0;" ::: "memory");
#pragma unroll
                for (int r = 0; r < 4; r++) red_cnt(&g_sync[(4 + r) * 32 + 1]);
                mbar_arrive(BAR(B_P3));
            }
            TS0(6);
        }
        const int wg = warp >> 2, wq = warp & 3;
        {
            const uint32_t MX = RED;
            const uint32_t LRED = RED + 512;
            const uint32_t OST = ACTB + 128, PST = ACTB;
            const uint32_t ALPHA = RED + 1536, MRUN = RED + 1664;
            float o[4][16];
            float lsum[8];
#pragma unroll
            for (int k = 0; k < 8; k++) lsum[k] = 0.f;
            if (t < 32) stsf(MRUN + t * 4, -INFINITY);
            mbar_wait(BAR(B_QABS));
            TS0(7);
            float s[16];
            auto qk = [&](int c0, int c1) {
                uint32_t da = desc_lo(SB0 + OFF_KV) + wg * (65536 >> 4) + c0 * (8192 >> 4), db = desc_lo(SB0 + OFF_X) + c0 * (4096 >> 4);
#pragma unroll 1
                for (int cb = c0; cb < c1; cb++) {
                    mbar_wait(BAR(B_KV) + (wg * 8 + cb) * 8);
                    wg_fence();
#pragma unroll
                    for (int k = 0; k < 4; k++) wgmma_n32<0>(s, da + k * 2, db + k * 2, (cb | k) != 0);
                    wg_commit();
                    da += 8192 >> 4;
                    db += 4096 >> 4;
                }
            };
            if (wg == 1) qk(0, QK_EARLY);
#pragma unroll 1
            for (int tile = 0; tile < 2; tile++) {
                if (wg == tile) {
                    qk(tile == 0 ? 0 : QK_EARLY, 8);
                    wg_wait0();
                    reg_fence(s);
                    if (tile == 1) {
                        __syncwarp();
                        if (lane == 0) {
                            mbar_arrive(BAR(B_XFREE));
                            mbar_arrive(BAR(B_KV0FREE));
                            asm volatile("mbarrier.arrive.relaxed.cluster.shared::cluster.b64 _, [%0];" ::"r"(mapa(BAR(B_PEER0), rank ^ 1)) : "memory");
                        }
                    }
                    if (wq == 0) TS(8 + tile * 2);
                    float m[8];
#pragma unroll
                    for (int jb = 0; jb < 4; jb++) {
                        m[2 * jb] = fmaxf(s[4 * jb], s[4 * jb + 2]);
                        m[2 * jb + 1] = fmaxf(s[4 * jb + 1], s[4 * jb + 3]);
                    }
                    {
                        const bool u4 = lane & 16, u3 = lane & 8, u2 = lane & 4;
                        float h4[4], h2[2];
#pragma unroll
                        for (int k = 0; k < 4; k++) h4[k] = fmaxf(u4 ? m[k + 4] : m[k], __shfl_xor_sync(~0u, u4 ? m[k] : m[k + 4], 16));
#pragma unroll
                        for (int k = 0; k < 2; k++) h2[k] = fmaxf(u3 ? h4[k + 2] : h4[k], __shfl_xor_sync(~0u, u3 ? h4[k] : h4[k + 2], 8));
                        const float h1 = fmaxf(u2 ? h2[1] : h2[0], __shfl_xor_sync(~0u, u2 ? h2[0] : h2[1], 4));
                        stsf(MX + (wq * 32 + 8 * (g >> 1) + 2 * q + (g & 1)) * 4, h1);
                    }
                    if (tile == 0) asm volatile("bar.sync 2, 128;" ::: "memory"); else asm volatile("bar.sync 3, 128;" ::: "memory");
                    const float mold = ldsf(MRUN + tile * 128 + lane * 4);
                    const float mnew = fmaxf(fmaxf(fmaxf(ldsf(MX + lane * 4), ldsf(MX + 128 + lane * 4)), fmaxf(ldsf(MX + 256 + lane * 4), ldsf(MX + 384 + lane * 4))), mold);
                    uint32_t lo[4], hi[4];
#pragma unroll
                    for (int jb = 0; jb < 4; jb++) {
                        const float m0 = __shfl_sync(~0u, mnew, 8 * jb + 2 * q), m1 = __shfl_sync(~0u, mnew, 8 * jb + 2 * q + 1);
                        lo[jb] = pack_bf16(ex2(s[4 * jb] - m0), ex2(s[4 * jb + 1] - m1));
                        hi[jb] = pack_bf16(ex2(s[4 * jb + 2] - m0), ex2(s[4 * jb + 3] - m1));
                        lsum[2 * jb] = bf_lo(lo[jb]) + bf_lo(hi[jb]);
                        lsum[2 * jb + 1] = bf_hi(lo[jb]) + bf_hi(hi[jb]);
                    }
                    const uint32_t prow = sb + OFF_P + tile * 4096 + ((lane + 16 * rank) & 31) * 128;
                    stsm4t(prow + (((2 * wq) ^ (lane & 7)) << 4), lo[0], lo[1], lo[2], lo[3]);
                    stsm4t(prow + (((2 * wq + 1) ^ (lane & 7)) << 4), hi[0], hi[1], hi[2], hi[3]);
                    fence_async_smem();
                    if (wq == 0) { stsf(ALPHA + lane * 4, ex2(mold - mnew)); stsf(MRUN + (tile + 1) * 128 + lane * 4, mnew); }
                }
                bar_main();
                TS0(27 + tile);
                if (tile == 1) {
                    wg_wait0();
#pragma unroll
                    for (int mt = 0; mt < 4; mt++) reg_fence(o[mt]);
#pragma unroll
                    for (int jb = 0; jb < 4; jb++) {
                        const float2 a = ldsf2(ALPHA + ((8 * jb + 2 * q + 16 * rank) & 31) * 4);
#pragma unroll
                        for (int mt = 0; mt < 4; mt++) { o[mt][4 * jb] *= a.x; o[mt][4 * jb + 1] *= a.y; o[mt][4 * jb + 2] *= a.x; o[mt][4 * jb + 3] *= a.y; }
                    }
                }
                {
                    const uint32_t da = desc_lo(SB0 + OFF_KV) + tile * (65536 >> 4) + wg * (32768 >> 4), db = desc_lo(SB0 + OFF_P) + tile * (4096 >> 4);
                    wg_fence();
#pragma unroll
                    for (int mt = 0; mt < 4; mt++) {
#pragma unroll
                        for (int k = 0; k < 4; k++)
                            wgmma_n32<1>(o[mt], da + mt * (8192 >> 4) + k * (2048 >> 4), db + k * 2, tile | k);
                        wg_commit();
                    }
                }
                if (wg == tile) {
#pragma unroll
                    for (int of = 4; of <= 16; of <<= 1) {
#pragma unroll
                        for (int k = 0; k < 8; k++) lsum[k] += __shfl_xor_sync(~0u, lsum[k], of);
                    }
                    if (g == 0) {
#pragma unroll
                        for (int jb = 0; jb < 4; jb++)
                            asm volatile("st.shared.v2.f32 [%0], {%1,%2};" ::"r"(LRED + (warp * 32 + 8 * jb + 2 * q) * 4), "f"(lsum[2 * jb]), "f"(lsum[2 * jb + 1]) : "memory");
                    }
                    if (tile == 1) {
                        asm volatile("bar.sync 3, 128;" ::: "memory");
                        if (wq == 0) {
                            float l0 = 0.f, l1 = 0.f;
#pragma unroll
                            for (int w = 0; w < 4; w++) { l0 += ldsf(LRED + (w * 32 + lane) * 4); l1 += ldsf(LRED + ((w + 4) * 32 + lane) * 4); }
                            const float l = l0 * ldsf(ALPHA + lane * 4) + l1;
                            const float mf = ldsf(MRUN + 256 + lane * 4);
                            if ((lane >> 4) == (int)rank) {
                                asm volatile("st.shared.v2.f32 [%0], {%1,%2};" ::"r"(OST + (lane & 15) * 8), "f"(mf), "f"(l) : "memory");
                            } else {
                                mbar_wait(BAR(B_PEER0));
                                st_async2(mapa(PST + (lane & 15) * 8, rank ^ 1), mf, l, mapa(BAR(B_XST), rank ^ 1));
                            }
                            __syncwarp();
                            if (lane == 0) mbar_arrive(BAR(B_XST));
                        }
                    }
                }
                if (tile == 0 && wg == 0) {
                    wg_wait0();
                    __syncwarp();
                    if (lane == 0) {
                        mbar_arrive(BAR(B_KV0FREE));
                        asm volatile("mbarrier.arrive.relaxed.cluster.shared::cluster.b64 _, [%0];" ::"r"(mapa(BAR(B_PEER0), rank ^ 1)) : "memory");
                    }
                    TS0(9);
                }
            }
            mbar_wait(BAR(B_PEER0));
            {
                const uint32_t rx = mapa(sb + OFF_XCH + t * 16, rank ^ 1), rb = mapa(BAR(B_XCH), rank ^ 1);
                asm volatile("wgmma.wait_group.sync.aligned 3;" ::: "memory");
                reg_fence(o[0]);
                st_async4(rx, pack_bf16(o[0][8], o[0][9]), pack_bf16(o[0][10], o[0][11]), pack_bf16(o[0][12], o[0][13]), pack_bf16(o[0][14], o[0][15]), rb);
                asm volatile("wgmma.wait_group.sync.aligned 2;" ::: "memory");
                reg_fence(o[1]);
                st_async4(rx + 4096, pack_bf16(o[1][8], o[1][9]), pack_bf16(o[1][10], o[1][11]), pack_bf16(o[1][12], o[1][13]), pack_bf16(o[1][14], o[1][15]), rb);
                asm volatile("wgmma.wait_group.sync.aligned 1;" ::: "memory");
                reg_fence(o[2]);
                st_async4(rx + 8192, pack_bf16(o[2][8], o[2][9]), pack_bf16(o[2][10], o[2][11]), pack_bf16(o[2][12], o[2][13]), pack_bf16(o[2][14], o[2][15]), rb);
                wg_wait0();
                reg_fence(o[3]);
                st_async4(rx + 12288, pack_bf16(o[3][8], o[3][9]), pack_bf16(o[3][10], o[3][11]), pack_bf16(o[3][12], o[3][13]), pack_bf16(o[3][14], o[3][15]), rb);
            }
            TS0(11);
            mbar_wait(BAR(B_XST));
            float ca[4], cb[4];
#pragma unroll
            for (int k = 0; k < 4; k++) {
                const int n = 8 * (k >> 1) + 2 * q + (k & 1);
                const float2 so = ldsf2(OST + n * 8), sp = ldsf2(PST + n * 8);
                const float mx = fmaxf(so.x, sp.x);
                ca[k] = ex2(so.x - mx);
                cb[k] = ex2(sp.x - mx);
            }
#pragma unroll
            for (int mt = 0; mt < 4; mt++) {
                o[mt][0] *= ca[0]; o[mt][1] *= ca[1]; o[mt][2] *= ca[0]; o[mt][3] *= ca[1];
                o[mt][4] *= ca[2]; o[mt][5] *= ca[3]; o[mt][6] *= ca[2]; o[mt][7] *= ca[3];
            }
            if (warp == 0) {
                const float2 so = ldsf2(OST + (lane & 15) * 8), sp = ldsf2(PST + (lane & 15) * 8);
                const float mx = fmaxf(so.x, sp.x);
                const float l = so.y * ex2(so.x - mx) + sp.y * ex2(sp.x - mx);
                const float ln = __shfl_down_sync(~0u, l, 1), mn = __shfl_down_sync(~0u, mx, 1);
                if (lane < 16 && (lane & 1) == 0) put4(&g_stat[((rank * 4 + (lane >> 2)) * 64 + (i >> 1)) * 2 + ((lane >> 1) & 1)], mx, l, mn, ln, tag);
            }
            const uint32_t keep = (g == 0) ? 0xFFFEFFFEu : 0xFFFFFFFFu;
            const uint32_t tg = (g == 0) ? ((ep & 1u) ? 0u : 0x00010001u) : 0u;
            const int hl = lane & 15, mi2 = lane >> 4;
            mbar_wait(BAR(B_XCH));
            TS0(46);
#pragma unroll
            for (int mt = 0; mt < 4; mt++) {
                const uint4 r = lds128(sb + OFF_XCH + mt * 4096 + t * 16);
                const uint32_t lo0 = (pack_bf16(o[mt][0] + cb[0] * bf_lo(r.x), o[mt][1] + cb[1] * bf_hi(r.x)) & keep) | tg;
                const uint32_t hi0 = (pack_bf16(o[mt][2] + cb[0] * bf_lo(r.y), o[mt][3] + cb[1] * bf_hi(r.y)) & keep) | tg;
                const uint32_t lo1 = (pack_bf16(o[mt][4] + cb[2] * bf_lo(r.z), o[mt][5] + cb[3] * bf_hi(r.z)) & keep) | tg;
                const uint32_t hi1 = (pack_bf16(o[mt][6] + cb[2] * bf_lo(r.w), o[mt][7] + cb[3] * bf_hi(r.w)) & keep) | tg;
                const uint32_t row = sb + OFF_STG + (wg * 2 + (mt >> 1)) * 4096 + hl * 256;
                const int ch = (mt & 1) * 8 + wq * 2 + mi2;
                stsm4t(row + ((ch ^ (hl & 7)) << 4), lo0, lo1, hi0, hi1);
            }
            fence_async_smem();
            if (wg == 0) asm volatile("bar.sync 2, 128;" ::: "memory"); else asm volatile("bar.sync 3, 128;" ::: "memory");
            if (warp == 4) TS(47);
            if (wq == 0 && lane == 0) {
                bulk_s2g(&g_part[i * 1024 + wg * 512], sb + OFF_STG + wg * 8192, 8192);
                asm volatile("cp.async.bulk.commit_group;" ::: "memory");
                asm volatile("cp.async.bulk.wait_group 0;" ::: "memory");
                if (atomicAdd(reinterpret_cast<unsigned int*>(smem + OFF_MISC + 236), 1u) == 1u) red_cnt(&g_sync[bb * 32 + 1]);
            }
            TS0(12);
        }
        mbar_wait(BAR(B_CLR2));
        const uint32_t SCR = sb + OFF_SCR;
        {
            const int b = warp >> 1;
            const uint32_t ptag = par;
            const int pi = lane >> 3, v = (warp & 1) * 8 + (lane & 7);
            const uint4* sp = &g_stat[((hh >> 2) * 64 + b * 16 + (lane & 15)) * 2 + ((hh >> 1) & 1)];
            const uint4* src = &g_part[(2 * (b * 16 + pi) + (hh >> 4)) * 1024 + (jj * 16 + (hh & 15)) * 16 + v];
            float acc[8];
            int it = 0;
            bool ok;
            if (warp != 0) mbar_wait_n(BAR(B_WUV), 4);
            if (warp == 0) {
                const unsigned int target = (ep + 1u) * 32u;
                {
                    const unsigned int t_poll = lds32(MISC + 232) + GATE_NS;
#pragma unroll 1
                    while ((int)(gtimer_lo() - t_poll) < 0 && ++it < SPIN_LIMIT) {}
                    it = 0;
                }
#pragma unroll 1
                while (!__all_sync(~0u, (int)(ld_cnt(&g_sync[(lane & 3) * 32 + 1]) - target) >= 0) && ++it < SPIN_LIMIT) {}
                it = 0;
                if (lane == 0) mbar_arrive(BAR(B_G4));
            }
            bar_main();
            gemv_y_load(afr);
            TS0(13);
#pragma unroll 1
            do {
                const uint4 su = ld128(sp);
                uint4 r[4];
#pragma unroll
                for (int k = 0; k < 4; k++) r[k] = ld128(src + (size_t)k * 8 * 1024);
                ok = (su.x & 3u) == tag;
                const float mi = (hh & 1) ? __uint_as_float(su.z) : __uint_as_float(su.x & ~3u), li = (hh & 1) ? __uint_as_float(su.w) : __uint_as_float(su.y);
                float mx = mi;
#pragma unroll
                for (int of = 8; of; of >>= 1) mx = fmaxf(mx, __shfl_xor_sync(~0u, mx, of));
                float wi = ex2(mi - mx);
                float L = wi * li;
#pragma unroll
                for (int of = 8; of; of >>= 1) L += __shfl_xor_sync(~0u, L, of);
                wi = __fdividef(wi, L);
#pragma unroll
                for (int k = 0; k < 8; k++) acc[k] = 0.f;
#pragma unroll
                for (int k = 0; k < 4; k++) {
                    const float w = __shfl_sync(~0u, wi, 4 * k + pi);
                    ok = ok & ((r[k].x & 1u) == ptag);
                    acc[0] += w * bf_lo(r[k].x); acc[1] += w * bf_hi(r[k].x);
                    acc[2] += w * bf_lo(r[k].y); acc[3] += w * bf_hi(r[k].y);
                    acc[4] += w * bf_lo(r[k].z); acc[5] += w * bf_hi(r[k].z);
                    acc[6] += w * bf_lo(r[k].w); acc[7] += w * bf_hi(r[k].w);
                }
            } while (!__all_sync(~0u, ok) && ++it < SPIN_LIMIT);
            {
                const bool u4 = lane & 16, u3 = lane & 8;
                float h4[4], h2[2];
#pragma unroll
                for (int k = 0; k < 4; k++) h4[k] = (u4 ? acc[k + 4] : acc[k]) + __shfl_xor_sync(~0u, u4 ? acc[k] : acc[k + 4], 16);
#pragma unroll
                for (int k = 0; k < 2; k++) h2[k] = (u3 ? h4[k + 2] : h4[k]) + __shfl_xor_sync(~0u, u3 ? h4[k] : h4[k + 2], 8);
                const int ch = v ^ (hh & 7);
                sts32(ACT + b * 272 + (ch * 8 + (u4 ? 4 : 0) + (u3 ? 2 : 0)) * 2, pack_bf16(h2[0], h2[1]));
            }
            bar_main();
            TS0(14);
        }
        gemv_y_put(afr, &g_C[i * 128], ACT, tag);
        TS0(17);
        mbar_wait_n(BAR(B_WO), 4);
        {
            const int blk = lane >> 3, r8 = lane & 7;
            const uint32_t wb = sb + OFF_X + warp * 4096 + ((blk >> 1) * 8 + r8) * 128;
#pragma unroll
            for (int mt = 0; mt < 4; mt++) {
                const uint32_t co = ((2 * mt + (blk & 1)) ^ r8) << 4;
                ldsm4t(afr[2 * mt], wb + co);
                ldsm4t(afr[2 * mt + 1], wb + 16 * 128 + co);
            }
        }
        if (warp == 0) {
            const float4 a = get4sum4(&g_C[hh * 4 * 128 + jj * 32 + lane], 128, tag);
            sts_frag(ACTB, 80, (t >> 4) * 16 + vrr, vb0, a.x, a.y, a.z, a.w);
        }
        bar_main();
        TS0(16);
        {
            uint32_t b[4];
            ldsm4(b, ACTB + (lane & 3) * 80 + (lane >> 3) * 16);
            uint32_t px[4], py[4];
#pragma unroll
            for (int mt = 0; mt < 4; mt++) {
                float d[4] = {0.f, 0.f, 0.f, 0.f};
                mma16816(d, afr[2 * mt], b[0], b[1]);
                mma16816(d, afr[2 * mt + 1], b[2], b[3]);
                px[mt] = (pack_bf16(d[0], d[1]) & ~1u) | par;
                py[mt] = pack_bf16(d[2], d[3]);
            }
            if (q < 2) {
                uint2* dst = &g_O[i * 512 + warp * 64 + g * 2 + q];
#pragma unroll
                for (int mt = 0; mt < 4; mt++) st64(dst + mt * 16, px[mt], py[mt]);
            }
            TS0(18);
        }
        const int V = i * 4 + (t & 3);
        const int vm = (V >> 4) * 16 + ((V & 15) >> 1), vb = (V & 1) * 2;
        float4 x1 = make_float4(0.f, 0.f, 0.f, 0.f);
        {
            mbar_wait(BAR(B_MODV));
            const float4 r = reduce16(g_O, 128, par, G6ADELAY);
            if (t < 4) {
                const float4 x0 = ldsf4(MISC + 32 + t * 16), ga = ldsf4(MISC + 96 + t * 16);
                x1 = make_float4(x0.x + ga.x * r.x, x0.y + ga.y * r.y, x0.z + ga.z * r.z, x0.w + ga.w * r.w);
                put2(&g_X1[i * 16 + t], x1.x, x1.y, x1.z, x1.w, par);
            }
            TS0(19);
        }
        if (i < NFFN) {
            float4 mv[4];
#pragma unroll
            for (int k = 0; k < 4; k++) {
                uint4 u = lds128(sb + OFF_SBCB + (t + 256 * k) * 16);
                int it = 0;
                while ((u.x & 3u) != tag && ++it < SPIN_LIMIT) u = ld128(&g_M[512 + t + 256 * k]);
                mv[k] = as_f4(u);
            }
            mbar_wait_n(BAR(B_W1), 4);
            {
                const int blk = lane >> 3, r8 = lane & 7;
                const uint32_t w1r = sb + OFF_Z + (warp * 64 + (blk >> 1) * 8 + r8) * 32 + (((blk & 1) ^ ((r8 >> 2) & 1)) << 4);
                const uint32_t w2r = sb + OFF_W2 + warp * 2048 + ((blk >> 1) * 8 + r8) * 128;
#pragma unroll
                for (int k = 0; k < 4; k++) {
                    ldsm4t(afr[k], w1r + k * 512);
                    ldsm4t(afr[4 + k], w2r + (((2 * k + (blk & 1)) ^ r8) << 4));
                }
            }
            TS0(21);
            uint2 ua, ub;
            {
                int it = 0;
#pragma unroll 1
                do { ua = ld64(&g_X1[(t >> 2) * 16 + (t & 3)]); ub = ld64(&g_X1[(t >> 2) * 16 + (t & 3) + 1024]); } while (!__all_sync(~0u, (((ua.x ^ par) | (ub.x ^ par)) & 1u) == 0) && ++it < SPIN_LIMIT);
            }
            const float4 a = as_f4(ua), b = as_f4(ub);
            float s0 = (a.x + a.z) + (b.x + b.z), s1 = (a.y + a.w) + (b.y + b.w);
            float q0 = (a.x * a.x + a.z * a.z) + (b.x * b.x + b.z * b.z), q1 = (a.y * a.y + a.w * a.w) + (b.y * b.y + b.w * b.w);
#pragma unroll
            for (int of = 2; of <= 16; of <<= 1) {
                s0 += __shfl_xor_sync(~0u, s0, of); s1 += __shfl_xor_sync(~0u, s1, of);
                q0 += __shfl_xor_sync(~0u, q0, of); q1 += __shfl_xor_sync(~0u, q1, of);
            }
            const uint32_t ST = SCR + 1024, ACT2 = SCR + 4096;
            if (lane < 2) stsf4(ST + (warp * 2 + lane) * 16, make_float4(s0, q0, s1, q1));
            bar_main();
            TS0(20);
            float4 tot = make_float4(0.f, 0.f, 0.f, 0.f);
#pragma unroll
            for (int w = 0; w < 8; w++) add4(tot, ldsf4(ST + (w * 2 + (t & 1)) * 16));
            const float mean0 = tot.x * (1.f / 512.f), mean1 = tot.z * (1.f / 512.f);
            const float r0 = rsqrtf(fmaxf(tot.y * (1.f / 512.f) - mean0 * mean0, 0.f) + 1e-5f);
            const float r1 = rsqrtf(fmaxf(tot.w * (1.f / 512.f) - mean1 * mean1, 0.f) + 1e-5f);
            const int m0 = (t >> 4) * 16 + vrr;
            sts_frag(ACT2, 1040, m0, vb0, (a.x - mean0) * r0 * (1.f + mv[2].x) + mv[0].x, (a.y - mean1) * r1 * (1.f + mv[2].y) + mv[0].y,
                     (a.z - mean0) * r0 * (1.f + mv[2].z) + mv[0].z, (a.w - mean1) * r1 * (1.f + mv[2].w) + mv[0].w);
            sts_frag(ACT2, 1040, m0 + 256, vb0, (b.x - mean0) * r0 * (1.f + mv[3].x) + mv[1].x, (b.y - mean1) * r1 * (1.f + mv[3].y) + mv[1].y,
                     (b.z - mean0) * r0 * (1.f + mv[3].z) + mv[1].z, (b.w - mean1) * r1 * (1.f + mv[3].w) + mv[1].w);
            bar_main();
            float d[4] = {0.f, 0.f, 0.f, 0.f};
            {
                const uint32_t brow = ACT2 + (lane & 3) * 1040 + (warp * 64 + (lane >> 3) * 8) * 2;
                uint32_t b0[4], b1[4];
                ldsm4(b0, brow);
                ldsm4(b1, brow + 64);
                float e[4] = {0.f, 0.f, 0.f, 0.f};
                mma16816(d, afr[0], b0[0], b0[1]);
                mma16816(e, afr[1], b0[2], b0[3]);
                mma16816(d, afr[2], b1[0], b1[1]);
                mma16816(e, afr[3], b1[2], b1[3]);
                d[0] += e[0]; d[1] += e[1]; d[2] += e[2]; d[3] += e[3];
            }
            const uint32_t HR = SCR + 2048;
            if (q < 2) {
                const uint32_t a0 = HR + (warp * 64 + (2 * q) * 16 + (g >> 1) * 4 + (g & 1)) * 4;
                stsf(a0, d[0]); stsf(a0 + 64, d[1]); stsf(a0 + 8, d[2]); stsf(a0 + 72, d[3]);
            }
            bar_main();
            float4 hs = ldsf4(HR + ((g & 3) * 16 + q * 4) * 4);
#pragma unroll
            for (int w = 1; w < 8; w++) add4(hs, ldsf4(HR + (w * 64 + (g & 3) * 16 + q * 4) * 4));
            const uint32_t b0r = pack_bf16(fmaxf(hs.x, 0.f), fmaxf(hs.y, 0.f)), b1r = pack_bf16(fmaxf(hs.z, 0.f), fmaxf(hs.w, 0.f));
            TS0(22);
            uint32_t px[4], py[4];
#pragma unroll
            for (int mt = 0; mt < 4; mt++) {
                float e[4] = {0.f, 0.f, 0.f, 0.f};
                mma16816(e, afr[4 + mt], b0r, b1r);
                px[mt] = (pack_bf16(e[0], e[1]) & ~1u) | par;
                py[mt] = pack_bf16(e[2], e[3]);
            }
            if (q < 2) {
                uint2* dst = &g_F[i * 512 + warp * 64 + g * 2 + q];
#pragma unroll
                for (int mt = 0; mt < 4; mt++) st64(dst + mt * 16, px[mt], py[mt]);
            }
            TS0(23);
        }
        {
            const float4 r = reduce16(g_F, NFFN, par, i < NFFN ? HOPDELAY : FFNDELAY);
            if (t < 4) {
                const float4 gb = ldsf4(MISC + 96 + 64 + t * 16);
                p.out[vb * 512 + vm] = __float2bfloat16_rn(x1.x + gb.x * r.x);
                p.out[(vb + 1) * 512 + vm] = __float2bfloat16_rn(x1.y + gb.y * r.y);
                p.out[vb * 512 + vm + 8] = __float2bfloat16_rn(x1.z + gb.z * r.z);
                p.out[(vb + 1) * 512 + vm + 8] = __float2bfloat16_rn(x1.w + gb.w * r.w);
            }
            if (i == 0 && t < NSYNC) g_sync[t * 32] = ep + 1u;
            TS0(24);
        }
    }
}

typedef CUresult (*EncodeFn)(CUtensorMap*, CUtensorMapDataType, cuuint32_t, void*, const cuuint64_t*, const cuuint64_t*, const cuuint32_t*,
                             const cuuint32_t*, CUtensorMapInterleave, CUtensorMapSwizzle, CUtensorMapL2promotion, CUtensorMapFloatOOBfill);

void make_map(EncodeFn enc, CUtensorMap* m, const void* base, int rank, const cuuint64_t* dims, const cuuint64_t* strides, const cuuint32_t* box,
              CUtensorMapSwizzle sw) {
    cuuint32_t es[3] = {1, 1, 1};
    CUresult r = enc(m, CU_TENSOR_MAP_DATA_TYPE_BFLOAT16, rank, const_cast<void*>(base), dims, strides, box, es, CU_TENSOR_MAP_INTERLEAVE_NONE, sw,
                     CU_TENSOR_MAP_L2_PROMOTION_NONE, CU_TENSOR_MAP_FLOAT_OOB_FILL_NONE);
    if (r != CUDA_SUCCESS) fprintf(stderr, "cuTensorMapEncodeTiled failed: %d\n", (int)r);
}
void map2d(EncodeFn enc, CUtensorMap* m, const void* base, uint64_t rows, uint64_t cols, uint32_t boxr, uint32_t boxc, CUtensorMapSwizzle sw) {
    cuuint64_t dims[2] = {cols, rows};
    cuuint64_t strides[1] = {cols * 2};
    cuuint32_t box[2] = {boxc, boxr};
    make_map(enc, m, base, 2, dims, strides, box, sw);
}
void map3d(EncodeFn enc, CUtensorMap* m, const void* base, uint64_t rows, uint32_t boxr, uint32_t boxb) {
    cuuint64_t dims[3] = {64, rows, 8};
    cuuint64_t strides[2] = {1024, 128};
    cuuint32_t box[3] = {64, boxr, boxb};
    make_map(enc, m, base, 3, dims, strides, box, CU_TENSOR_MAP_SWIZZLE_128B);
}

}

extern "C" void kernel_launch(void* const* d_in, const int* in_sizes, int n_in, void* d_out, int out_size) {
    (void)in_sizes; (void)n_in; (void)out_size;
    static EncodeFn enc = nullptr;
    static void* qabs_ptr = nullptr;
    static bool fits = false;
    if (!enc) {
        void* fn = nullptr;
        cudaDriverEntryPointQueryResult st;
        cudaGetDriverEntryPoint("cuTensorMapEncodeTiled", &fn, cudaEnableDefault, &st);
        enc = (EncodeFn)fn;
        cudaFuncSetAttribute(fused_kernel, cudaFuncAttributeMaxDynamicSharedMemorySize, SMEM_BYTES);
        cudaGetSymbolAddress(&qabs_ptr, g_qabs);
        cudaLaunchConfig_t cfg = {};
        cfg.gridDim = dim3(NCTA);
        cfg.blockDim = dim3(NTHREADS);
        cfg.dynamicSmemBytes = SMEM_BYTES;
        cudaLaunchAttribute at[1];
        at[0].id = cudaLaunchAttributeClusterDimension;
        at[0].val.clusterDim.x = 2; at[0].val.clusterDim.y = 1; at[0].val.clusterDim.z = 1;
        cfg.attrs = at;
        cfg.numAttrs = 1;
        int nclusters = 0;
        if (cudaOccupancyMaxActiveClusters(&nclusters, fused_kernel, &cfg) != cudaSuccess) { (void)cudaGetLastError(); nclusters = NCTA / 2; }
        fits = nclusters >= NCTA / 2;
        if (!fits) fprintf(stderr, "fused_kernel: only %d of %d clusters can be resident on this device\n", nclusters, NCTA / 2);
    }
    if (!enc || !fits) return;
    Params p;
    map2d(enc, &p.kv, d_in[1], 16384, 512, 64, 64, CU_TENSOR_MAP_SWIZZLE_128B);
    map2d(enc, &p.wq, d_in[2], 512, 4096, 64, 64, CU_TENSOR_MAP_SWIZZLE_128B);
    map2d(enc, &p.wuk, d_in[3], 512, 4096, 64, 64, CU_TENSOR_MAP_SWIZZLE_128B);
    map2d(enc, &p.wuv, d_in[4], 512, 4096, 64, 64, CU_TENSOR_MAP_SWIZZLE_128B);
    map3d(enc, &p.wo, d_in[5], 4096, 32, 2);
    map2d(enc, &p.w1, d_in[7], 512, 1376, 256, 16, CU_TENSOR_MAP_SWIZZLE_32B);
    map3d(enc, &p.w2, d_in[8], 1376, 16, 4);
    map2d(enc, &p.wmod, d_in[10], 512, 3072, 256, 16, CU_TENSOR_MAP_SWIZZLE_32B);
    map3d(enc, &p.qabs, qabs_ptr, 128, 32, 4);
    map2d(enc, &p.wmoda, d_in[10], 512, 3072, 128, 16, CU_TENSOR_MAP_SWIZZLE_32B);
    p.x = (const __nv_bfloat16*)d_in[0];
    p.c = (const __nv_bfloat16*)d_in[9];
    p.out = (__nv_bfloat16*)d_out;
    fused_kernel<<<NCTA, NTHREADS, SMEM_BYTES, cudaStreamPerThread>>>(p);
}
```

```cpp
#include <cuda_runtime.h>
#include <cuda_bf16.h>
#include <cuda.h>
#include <stdint.h>
#include <stdio.h>

namespace {

constexpr int NCTA = 128;
constexpr int NTHREADS = 320;
constexpr int NFFN = 86;
#define WINDOW 5
#define DT_0 500
#define DT_F 340
#define DT_S 325
#define DT_T 320
#define DT_T2 300
#define QK_EARLY 4
#define GATE_NS 3600
#define STAT_LEAD 200
#define G6ADELAY 450
#define HOPDELAY 300
#define FFNDELAY 2300

constexpr uint32_t OFF_KV = 0;
constexpr uint32_t OFF_X = 131072;
constexpr uint32_t OFF_Y = 163840;
constexpr uint32_t OFF_Z = 196608;
constexpr uint32_t OFF_P = 212992;
constexpr uint32_t OFF_S = 221184;
constexpr uint32_t OFF_ACT = 225344;
constexpr uint32_t OFF_RED = 227648;
constexpr uint32_t OFF_BAR = 229696;
constexpr uint32_t OFF_MISC = 230208;
constexpr uint32_t SMEM_BYTES = 230720;
constexpr uint32_t OFF_STG = OFF_KV;
constexpr uint32_t OFF_XCH = OFF_KV + 16384;
constexpr uint32_t OFF_W2 = OFF_KV + 32768;
constexpr uint32_t OFF_SBCB = OFF_KV + 49152;
constexpr uint32_t OFF_SCR = OFF_KV + 65536;

enum {
    B_WQ = 0,
    B_WUK = 4,
    B_KV = 8,
    B_MOD = 24,
    B_WUV = 26,
    B_WO = 30,
    B_W1 = 34,
    B_W2 = 36,
    B_QABS = 38,
    B_YFREE = 39,
    B_XFREE = 40,
    B_ZFREE = 41,
    B_KV0FREE = 42,
    B_P3 = 43,
    B_CLR2 = 44,
    B_MODV = 45,
    B_WA = 46,
    B_EP = 47,
    B_PEER0 = 48,
    B_XCH = 49,
    B_G4 = 50,
    B_XST = 51,
    B_COUNT = 52
};

struct alignas(64) Params {
    CUtensorMap kv, wq, wuk, wuv, wo, w1, w2, wmod, qabs, wmoda;
    const __nv_bfloat16* x;
    const __nv_bfloat16* c;
    __nv_bfloat16* out;
};

__device__ __align__(128) uint4 g_H[128 * 32];
__device__ __align__(128) uint4 g_Q[128 * 128];
__device__ __align__(128) __nv_bfloat16 g_qabs[4 * 32 * 512];
__device__ __align__(128) uint4 g_part[128 * 4 * 16 * 16];
__device__ __align__(128) uint4 g_stat[8 * 64 * 2];
__device__ __align__(128) uint4 g_C[128 * 128];
__device__ __align__(128) uint2 g_O[128 * 512];
__device__ __align__(128) uint2 g_X1[128 * 16];
__device__ __align__(128) uint2 g_F[NFFN * 512];
__device__ __align__(128) uint4 g_M[4 * 512];
constexpr int NSYNC = 8;
__device__ __align__(128) unsigned int g_sync[NSYNC * 32];

__device__ __forceinline__ uint32_t smem_u32(const void* p) { return (uint32_t)__cvta_generic_to_shared(p); }
__device__ __forceinline__ void mbar_init(uint32_t bar, int cnt) { asm volatile("mbarrier.init.shared::cta.b64 [%0], %1;" ::"r"(bar), "r"(cnt) : "memory"); }
__device__ __forceinline__ void mbar_expect_tx(uint32_t bar, uint32_t bytes) { asm volatile("mbarrier.arrive.expect_tx.shared::cta.b64 _, [%0], %1;" ::"r"(bar), "r"(bytes) : "memory"); }
__device__ __forceinline__ void mbar_arrive(uint32_t bar) { asm volatile("mbarrier.arrive.shared::cta.b64 _, [%0];" ::"r"(bar) : "memory"); }
constexpr int SPIN_LIMIT = 1 << 20;
__device__ __forceinline__ void mbar_wait(uint32_t bar) {
    asm volatile("{\n.reg .pred p;\n.reg .u32 n;\nmov.u32 n, 0;\n"
                 "LW:\nmbarrier.try_wait.parity.shared::cta.b64 p, [%0], 0;\n@p bra LD;\n"
                 "add.u32 n, n, 1;\nsetp.lt.u32 p, n, 262144;\n@p bra LW;\nLD:\n}" ::"r"(bar) : "memory");
}
__device__ __forceinline__ void mbar_wait_n(uint32_t bar, int n) {
#pragma unroll 1
    for (int k = 0; k < n; k++) mbar_wait(bar + k * 8);
}
__device__ __forceinline__ void bar_main() { asm volatile("bar.sync 1, 256;" ::: "memory"); }
__device__ __forceinline__ void fence_async_smem() { asm volatile("fence.proxy.async.shared::cta;" ::: "memory"); }

__device__ __forceinline__ uint4 ld128(const uint4* p) {
    uint4 v;
    asm volatile("{\n.reg .b128 t;\n.reg .b64 lo, hi;\nld.relaxed.gpu.global.b128 t, [%4];\nmov.b128 {lo, hi}, t;\nmov.b64 {%0,%1}, lo;\nmov.b64 {%2,%3}, hi;\n}"
                 : "=r"(v.x), "=r"(v.y), "=r"(v.z), "=r"(v.w) : "l"(p) : "memory");
    return v;
}
__device__ __forceinline__ void st128(uint4* p, uint4 v) {
    asm volatile("{\n.reg .b128 t;\n.reg .b64 lo, hi;\nmov.b64 lo, {%1,%2};\nmov.b64 hi, {%3,%4};\nmov.b128 t, {lo, hi};\nst.relaxed.gpu.global.b128 [%0], t;\n}"
                 ::"l"(p), "r"(v.x), "r"(v.y), "r"(v.z), "r"(v.w) : "memory");
}
__device__ __forceinline__ uint4 ldnc128_if(const void* p, bool c) {
    uint4 v;
    asm volatile("{\n.reg .pred p;\nsetp.ne.u32 p, %5, 0;\nmov.u32 %0, 0;\nmov.u32 %1, 0;\nmov.u32 %2, 0;\nmov.u32 %3, 0;\n@p ld.global.nc.v4.u32 {%0,%1,%2,%3}, [%4];\n}"
                 : "=r"(v.x), "=r"(v.y), "=r"(v.z), "=r"(v.w) : "l"(p), "r"((uint32_t)c));
    return v;
}
__device__ __forceinline__ uint32_t ldnc32(const void* p) { uint32_t v; asm volatile("ld.global.nc.u32 %0, [%1];" : "=r"(v) : "l"(p)); return v; }
__device__ __forceinline__ uint32_t ldnc16(const void* p) { uint32_t v; asm volatile("ld.global.nc.u16 %0, [%1];" : "=r"(v) : "l"(p)); return v; }
__device__ __forceinline__ unsigned int ld_epoch(const unsigned int* p) { unsigned int v; asm volatile("ld.relaxed.gpu.global.u32 %0, [%1];" : "=r"(v) : "l"(p)); return v; }
__device__ __forceinline__ void put4(uint4* p, float a, float b, float c, float d, uint32_t tag) {
    st128(p, make_uint4((__float_as_uint(a) & ~3u) | tag, __float_as_uint(b), __float_as_uint(c), __float_as_uint(d)));
}
__device__ __forceinline__ float4 as_f4(uint4 v) {
    return make_float4(__uint_as_float(v.x & ~3u), __uint_as_float(v.y), __uint_as_float(v.z), __uint_as_float(v.w));
}
__device__ __forceinline__ void add4(float4& a, const float4& b) { a.x += b.x; a.y += b.y; a.z += b.z; a.w += b.w; }
__device__ __forceinline__ float4 get4(const uint4* p, bool act, uint32_t tag) {
    uint4 v = make_uint4(tag, 0, 0, 0);
    int it = 0;
#pragma unroll 1
    do { if (act) v = ld128(p); } while (!__all_sync(~0u, (v.x & 3u) == tag) && ++it < SPIN_LIMIT);
    return as_f4(v);
}
__device__ __forceinline__ uint2 ld64(const uint2* p) { uint2 v; asm volatile("{\n.reg .b64 t;\nld.relaxed.gpu.global.b64 t, [%2];\nmov.b64 {%0,%1}, t;\n}" : "=r"(v.x), "=r"(v.y) : "l"(p) : "memory"); return v; }
__device__ __forceinline__ void st64(uint2* p, uint32_t x, uint32_t y) { asm volatile("{\n.reg .b64 t;\nmov.b64 t, {%1,%2};\nst.relaxed.gpu.global.b64 [%0], t;\n}" ::"l"(p), "r"(x), "r"(y) : "memory"); }
__device__ __forceinline__ uint32_t pack_bf16(float lo, float hi);
__device__ __forceinline__ void put2(uint2* p, float a, float b, float c, float d, uint32_t par) { st64(p, (pack_bf16(a, b) & ~1u) | par, pack_bf16(c, d)); }
__device__ __forceinline__ float4 as_f4(uint2 v) {
    return make_float4(__uint_as_float(v.x << 16), __uint_as_float(v.x & 0xffff0000u), __uint_as_float(v.y << 16), __uint_as_float(v.y & 0xffff0000u));
}
__device__ __forceinline__ float4 get4sum4(const uint4* p0, int stride, uint32_t tag) {
    uint4 u0, u1, u2, u3;
    int it = 0;
#pragma unroll 1
    do { u0 = ld128(p0); u1 = ld128(p0 + stride); u2 = ld128(p0 + 2 * stride); u3 = ld128(p0 + 3 * stride); }
    while (!__all_sync(~0u, ((u0.x ^ tag) & 3u) == 0 && ((u1.x ^ tag) & 3u) == 0 && ((u2.x ^ tag) & 3u) == 0 && ((u3.x ^ tag) & 3u) == 0) && ++it < SPIN_LIMIT);
    float4 a = as_f4(u0), b = as_f4(u2);
    add4(a, as_f4(u1));
    add4(b, as_f4(u3));
    add4(a, b);
    return a;
}
__device__ __forceinline__ uint32_t pack_bf16(float lo, float hi) {
    uint32_t r;
    asm("cvt.rn.bf16x2.f32 %0, %1, %2;" : "=r"(r) : "f"(hi), "f"(lo));
    return r;
}
__device__ __forceinline__ float bf_lo(uint32_t u) { return __uint_as_float(u << 16); }
__device__ __forceinline__ float bf_hi(uint32_t u) { return __uint_as_float(u & 0xffff0000u); }
__device__ __forceinline__ float ex2(float x) { float y; asm("ex2.approx.ftz.f32 %0, %1;" : "=f"(y) : "f"(x)); return y; }

__device__ __forceinline__ void ldsm4(uint32_t (&r)[4], uint32_t addr) {
    asm volatile("ldmatrix.sync.aligned.m8n8.x4.shared.b16 {%0,%1,%2,%3}, [%4];" : "=r"(r[0]), "=r"(r[1]), "=r"(r[2]), "=r"(r[3]) : "r"(addr) : "memory");
}
__device__ __forceinline__ void ldsm4t(uint32_t (&r)[4], uint32_t addr) {
    asm volatile("ldmatrix.sync.aligned.m8n8.x4.trans.shared.b16 {%0,%1,%2,%3}, [%4];" : "=r"(r[0]), "=r"(r[1]), "=r"(r[2]), "=r"(r[3]) : "r"(addr) : "memory");
}
__device__ __forceinline__ void stsm4t(uint32_t addr, uint32_t r0, uint32_t r1, uint32_t r2, uint32_t r3) {
    asm volatile("stmatrix.sync.aligned.m8n8.x4.trans.shared.b16 [%0], {%1,%2,%3,%4};" ::"r"(addr), "r"(r0), "r"(r1), "r"(r2), "r"(r3) : "memory");
}
__device__ __forceinline__ void mma16816(float (&d)[4], const uint32_t (&a)[4], uint32_t b0, uint32_t b1) {
    asm volatile("mma.sync.aligned.m16n8k16.row.col.f32.bf16.bf16.f32 {%0,%1,%2,%3}, {%4,%5,%6,%7}, {%8,%9}, {%0,%1,%2,%3};"
                 : "+f"(d[0]), "+f"(d[1]), "+f"(d[2]), "+f"(d[3]) : "r"(a[0]), "r"(a[1]), "r"(a[2]), "r"(a[3]), "r"(b0), "r"(b1));
}
__device__ __forceinline__ void sts32(uint32_t a, uint32_t v) { asm volatile("st.shared.b32 [%0], %1;" ::"r"(a), "r"(v) : "memory"); }
__device__ __forceinline__ void sts16(uint32_t a, float v) {
    __nv_bfloat16 h = __float2bfloat16_rn(v);
    asm volatile("st.shared.b16 [%0], %1;" ::"r"(a), "h"(*reinterpret_cast<unsigned short*>(&h)) : "memory");
}
__device__ __forceinline__ void stsf(uint32_t a, float v) { asm volatile("st.shared.f32 [%0], %1;" ::"r"(a), "f"(v) : "memory"); }
__device__ __forceinline__ void stsf4(uint32_t a, float4 v) { asm volatile("st.shared.v4.f32 [%0], {%1,%2,%3,%4};" ::"r"(a), "f"(v.x), "f"(v.y), "f"(v.z), "f"(v.w) : "memory"); }
__device__ __forceinline__ uint32_t lds32(uint32_t a) { uint32_t v; asm volatile("ld.shared.b32 %0, [%1];" : "=r"(v) : "r"(a) : "memory"); return v; }
__device__ __forceinline__ float ldsf(uint32_t a) { float v; asm volatile("ld.shared.f32 %0, [%1];" : "=f"(v) : "r"(a) : "memory"); return v; }
__device__ __forceinline__ float2 ldsf2(uint32_t a) { float2 v; asm volatile("ld.shared.v2.f32 {%0,%1}, [%2];" : "=f"(v.x), "=f"(v.y) : "r"(a) : "memory"); return v; }
__device__ __forceinline__ float4 ldsf4(uint32_t a) { float4 v; asm volatile("ld.shared.v4.f32 {%0,%1,%2,%3}, [%4];" : "=f"(v.x), "=f"(v.y), "=f"(v.z), "=f"(v.w) : "r"(a) : "memory"); return v; }
__device__ __forceinline__ uint4 lds128(uint32_t a) { uint4 v; asm volatile("ld.shared.v4.b32 {%0,%1,%2,%3}, [%4];" : "=r"(v.x), "=r"(v.y), "=r"(v.z), "=r"(v.w) : "r"(a) : "memory"); return v; }

__device__ __forceinline__ void tma2d(uint32_t dst, const CUtensorMap* m, int c0, int c1, uint32_t bar, uint32_t bytes, uint64_t pol) {
    asm volatile("{\n.reg .pred p;\nelect.sync _|p, 0xffffffff;\n"
                 "@p mbarrier.arrive.expect_tx.shared::cta.b64 _, [%2], %6;\n"
                 "@p cp.async.bulk.tensor.2d.shared::cluster.global.mbarrier::complete_tx::bytes.L2::cache_hint [%0], [%1, {%3, %4}], [%2], %5;\n}"
                 ::"r"(dst), "l"(m), "r"(bar), "r"(c0), "r"(c1), "l"(pol), "r"(bytes) : "memory");
}
__device__ __forceinline__ void tma3d(uint32_t dst, const CUtensorMap* m, int c0, int c1, int c2, uint32_t bar, uint32_t bytes, uint64_t pol) {
    asm volatile("{\n.reg .pred p;\nelect.sync _|p, 0xffffffff;\n"
                 "@p mbarrier.arrive.expect_tx.shared::cta.b64 _, [%2], %7;\n"
                 "@p cp.async.bulk.tensor.3d.shared::cluster.global.mbarrier::complete_tx::bytes.L2::cache_hint [%0], [%1, {%3, %4, %5}], [%2], %6;\n}"
                 ::"r"(dst), "l"(m), "r"(bar), "r"(c0), "r"(c1), "r"(c2), "l"(pol), "r"(bytes) : "memory");
}
__device__ __forceinline__ void tma2d_na(uint32_t dst, const CUtensorMap* m, int c0, int c1, uint32_t bar, uint64_t pol) {
    asm volatile("{\n.reg .pred p;\nelect.sync _|p, 0xffffffff;\n"
                 "@p cp.async.bulk.tensor.2d.shared::cluster.global.mbarrier::complete_tx::bytes.L2::cache_hint [%0], [%1, {%3, %4}], [%2], %5;\n}"
                 ::"r"(dst), "l"(m), "r"(bar), "r"(c0), "r"(c1), "l"(pol) : "memory");
}
__device__ __forceinline__ uint32_t mapa(uint32_t addr, uint32_t rank) {
    uint32_t r;
    asm("mapa.shared::cluster.u32 %0, %1, %2;" : "=r"(r) : "r"(addr), "r"(rank));
    return r;
}
__device__ __forceinline__ void st_async4(uint32_t raddr, uint32_t a, uint32_t b, uint32_t c, uint32_t d, uint32_t rbar) {
    asm volatile("st.async.weak.shared::cluster.mbarrier::complete_tx::bytes.v4.b32 [%0], {%1,%2,%3,%4}, [%5];" ::"r"(raddr), "r"(a), "r"(b), "r"(c), "r"(d), "r"(rbar) : "memory");
}
__device__ __forceinline__ void st_async2(uint32_t raddr, float a, float b, uint32_t rbar) {
    asm volatile("st.async.weak.shared::cluster.mbarrier::complete_tx::bytes.v2.f32 [%0], {%1,%2}, [%3];" ::"r"(raddr), "f"(a), "f"(b), "r"(rbar) : "memory");
}
__device__ __forceinline__ void tma3d_mc(uint32_t dst, const CUtensorMap* m, int c0, int c1, int c2, uint32_t bar, uint32_t bytes) {
    asm volatile("{\n.reg .pred p;\nelect.sync _|p, 0xffffffff;\n"
                 "@p mbarrier.arrive.expect_tx.shared::cta.b64 _, [%2], %6;\n"
                 "@p cp.async.bulk.tensor.3d.shared::cluster.global.mbarrier::complete_tx::bytes.multicast::cluster [%0], [%1, {%3, %4, %5}], [%2], %7;\n}"
                 ::"r"(dst), "l"(m), "r"(bar), "r"(c0), "r"(c1), "r"(c2), "r"(bytes), "h"((unsigned short)3) : "memory");
}
__device__ __forceinline__ void bulk_s2g(void* dst, uint32_t src, uint32_t bytes) {
    asm volatile("cp.async.bulk.global.shared::cta.bulk_group [%0], [%1], %2;" ::"l"(dst), "r"(src), "r"(bytes) : "memory");
}
__device__ __forceinline__ void prefetch_map(const CUtensorMap* m) { asm volatile("prefetch.tensormap [%0];" ::"l"(m) : "memory"); }

constexpr uint32_t DESC_HI = 64u | (1u << 30);
__device__ __forceinline__ constexpr uint32_t desc_lo(uint32_t addr) { return ((addr & 0x3FFFF) >> 4) | (1u << 16); }
__device__ __forceinline__ void wg_fence() { asm volatile("wgmma.fence.sync.aligned;" ::: "memory"); }
__device__ __forceinline__ void wg_commit() { asm volatile("wgmma.commit_group.sync.aligned;" ::: "memory"); }
__device__ __forceinline__ void wg_wait0() { asm volatile("wgmma.wait_group.sync.aligned 0;" ::: "memory"); }
template <int TA>
__device__ __forceinline__ void wgmma_n32(float (&d)[16], uint32_t alo, uint32_t blo, int scale_d) {
    asm volatile("{\n.reg .pred p;\n.reg .b64 da, db;\nsetp.ne.b32 p, %18, 0;\nmov.b64 da, {%16, %20};\nmov.b64 db, {%17, %20};\n"
                 "wgmma.mma_async.sync.aligned.m64n32k16.f32.bf16.bf16 "
                 "{%0,%1,%2,%3,%4,%5,%6,%7,%8,%9,%10,%11,%12,%13,%14,%15}, da, db, p, 1, 1, %19, 0;\n}"
                 : "+f"(d[0]), "+f"(d[1]), "+f"(d[2]), "+f"(d[3]), "+f"(d[4]), "+f"(d[5]), "+f"(d[6]), "+f"(d[7]),
                   "+f"(d[8]), "+f"(d[9]), "+f"(d[10]), "+f"(d[11]), "+f"(d[12]), "+f"(d[13]), "+f"(d[14]), "+f"(d[15])
                 : "r"(alo), "r"(blo), "r"(scale_d), "n"(TA), "n"(DESC_HI));
}
template <int N>
__device__ __forceinline__ void reg_fence(float (&d)[N]) {
#pragma unroll
    for (int i = 0; i < N; i++) asm volatile("" : "+f"(d[i])::"memory");
}

#define TS(slot)
#define TS0(slot)

__device__ __forceinline__ unsigned int gtimer_lo() {
    unsigned long long t;
    asm volatile("mov.u64 %0, %globaltimer;" : "=l"(t));
    return (unsigned int)t;
}
__device__ __forceinline__ unsigned int clock32() { unsigned int c; asm volatile("mov.u32 %0, %clock;" : "=r"(c)); return c; }
__device__ __forceinline__ void spin(int cycles) {
    if (cycles <= 0) return;
    const unsigned int t0 = clock32();
#pragma unroll 1
    while (clock32() - t0 < (unsigned int)cycles) {}
}
__device__ __forceinline__ unsigned int ld_cnt(const unsigned int* p) {
    unsigned int v;
    asm volatile("ld.relaxed.gpu.global.u32 %0, [%1];" : "=r"(v) : "l"(p) : "memory");
    return v;
}
__device__ __forceinline__ void wait_cnt(const unsigned int* p, unsigned int target) {
    int it = 0;
#pragma unroll 1
    while ((int)(ld_cnt(p) - target) < 0) { if (++it > SPIN_LIMIT) break; }
}
__device__ __forceinline__ void red_cnt(unsigned int* p) { asm volatile("red.relaxed.gpu.global.add.u32 [%0], 1;" ::"l"(p) : "memory"); }

constexpr uint32_t SB0 = 1024;
__device__ __forceinline__ uint32_t smem_base() {
    extern __shared__ __align__(1024) uint8_t smem_dyn[];
    return smem_u32(smem_dyn);
}

__device__ __forceinline__ void gemv_y_load(uint32_t (&a)[8][4]) {
    const int lane = threadIdx.x & 31, warp = threadIdx.x >> 5;
    const int blk = lane >> 3, r8 = lane & 7;
    const int ch = (warp & 3) * 2 + (blk & 1);
    const uint32_t arow = smem_base() + OFF_Y + (warp >> 2) * 16384 + ((blk >> 1) * 8 + r8) * 128 + ((ch ^ r8) << 4);
#pragma unroll
    for (int k = 0; k < 8; k++) ldsm4t(a[k], arow + k * 16 * 128);
}
__device__ __forceinline__ void gemv_y_put(const uint32_t (&a)[8][4], uint4* dst, uint32_t act, uint32_t tag) {
    const int lane = threadIdx.x & 31, warp = threadIdx.x >> 5;
    const uint32_t brow = act + (lane & 3) * 272 + (lane >> 3) * 16;
    uint32_t b[4][4];
#pragma unroll
    for (int k = 0; k < 4; k++) ldsm4(b[k], brow + k * 64);
    float d[4] = {0.f, 0.f, 0.f, 0.f}, e[4] = {0.f, 0.f, 0.f, 0.f};
#pragma unroll
    for (int k = 0; k < 4; k++) {
        mma16816(d, a[2 * k], b[k][0], b[k][1]);
        mma16816(e, a[2 * k + 1], b[k][2], b[k][3]);
    }
    const uint32_t x = (__float_as_uint(d[0] + e[0]) & ~3u) | tag;
    const float y = d[1] + e[1], z = d[2] + e[2], w = d[3] + e[3];
    if ((lane & 3) < 2) st128(dst + warp * 16 + (lane >> 2) * 2 + (lane & 3), make_uint4(x, __float_as_uint(y), __float_as_uint(z), __float_as_uint(w)));
}

__device__ __forceinline__ void gemv_512x16(float (&d)[4], uint32_t tile, uint32_t act, int k0, int nk2, int lane) {
    const int blk = lane >> 3, r8 = lane & 7;
    uint32_t arow = tile + (k0 + (blk >> 1) * 8 + r8) * 32 + (((blk & 1) ^ ((r8 >> 2) & 1)) << 4);
    uint32_t brow = act + (r8 & 3) * 1040 + (k0 + blk * 8) * 2;
#pragma unroll 2
    for (int k2 = 0; k2 < nk2; k2++) {
        uint32_t b[4], a0[4], a1[4];
        ldsm4(b, brow);
        ldsm4t(a0, arow);
        ldsm4t(a1, arow + 512);
        mma16816(d, a0, b[0], b[1]);
        mma16816(d, a1, b[2], b[3]);
        brow += 64;
        arow += 1024;
    }
}

__device__ __noinline__ float4 reduce16(const uint2* base, int n, uint32_t par, int delay) {
    const int t = threadIdx.x, lane = t & 31, warp = t >> 5;
    const uint32_t SCR = smem_base() + OFF_SCR;
    const int pp = t >> 2;
    const uint2* p0 = base + (size_t)pp * 512 + blockIdx.x * 4 + (t & 3);
    const bool act1 = pp + 64 < n;
    spin(delay);
    uint2 u, v = make_uint2(par, 0);
    int it = 0;
#pragma unroll 1
    do { u = ld64(p0); if (act1) v = ld64(p0 + 64 * 512); } while (!__all_sync(~0u, (((u.x ^ par) | (v.x ^ par)) & 1u) == 0) && ++it < SPIN_LIMIT);
    float4 a = as_f4(u);
    if (act1) add4(a, as_f4(v));
#pragma unroll
    for (int of = 4; of <= 16; of <<= 1) {
        a.x += __shfl_xor_sync(~0u, a.x, of); a.y += __shfl_xor_sync(~0u, a.y, of);
        a.z += __shfl_xor_sync(~0u, a.z, of); a.w += __shfl_xor_sync(~0u, a.w, of);
    }
    if (lane < 4) stsf4(SCR + (warp * 4 + lane) * 16, a);
    bar_main();
    float4 r = make_float4(0.f, 0.f, 0.f, 0.f);
    if (t < 4) {
#pragma unroll
        for (int w = 0; w < 8; w++) add4(r, ldsf4(SCR + (w * 4 + t) * 16));
    }
    return r;
}
__device__ __forceinline__ void sts_frag(uint32_t base, uint32_t stride, int m, int b0, float x, float y, float z, float w) {
    const uint32_t a = base + b0 * stride + m * 2;
    sts16(a, x); sts16(a + stride, y); sts16(a + 16, z); sts16(a + stride + 16, w);
}

__global__ void __cluster_dims__(2, 1, 1) __launch_bounds__(NTHREADS, 1) fused_kernel(const __grid_constant__ Params p) {
    extern __shared__ __align__(1024) uint8_t smem[];
    const uint32_t sb = smem_base();
    const int t = threadIdx.x, lane = t & 31;
    const int warp = __shfl_sync(0xffffffffu, t >> 5, 0);
    const int i = blockIdx.x;
    const int hh = i >> 2, jj = i & 3;
    const int bb = i >> 5, chunk = i & 31;
    const uint32_t rank = i & 1;
    auto BAR = [&](int k) { return sb + OFF_BAR + k * 8; };
    const uint32_t MISC = sb + OFF_MISC;

    if (warp == 8) {
        if (lane == 0) {
            TS(0);
            prefetch_map(&p.wmoda);
            prefetch_map(&p.wq);
            mbar_init(BAR(B_WA), 1);
            mbar_init(BAR(0), 1);
            asm volatile("fence.mbarrier_init.release.cluster;" ::: "memory");
            fence_async_smem();
            mbar_expect_tx(BAR(B_WA), 8192);
        }
        __syncwarp();
        uint64_t pol;
        asm volatile("createpolicy.fractional.L2::evict_first.b64 %0, 1.0;" : "=l"(pol));
        tma2d_na(sb + OFF_Z, &p.wmoda, 16 * hh, jj * 128, BAR(B_WA), pol);
        tma2d_na(sb + OFF_Z + 4096, &p.wmoda, 512 + 16 * hh, jj * 128, BAR(B_WA), pol);
        tma2d(sb + OFF_Y, &p.wq, hh * 128, jj * 128, BAR(0), 8192, pol);
        unsigned int due = gtimer_lo() + DT_0;
        if (lane == 0) {
            if ((sb & 0xFFFFFFu) != SB0) __trap();
#pragma unroll
            for (int k = 1; k < 4; k++) mbar_init(BAR(k), 1);
            asm volatile("fence.mbarrier_init.release.cluster;" ::: "memory");
            fence_async_smem();
        }
        __syncwarp();
        asm volatile("bar.arrive 4, 320;" ::: "memory");
        auto pace_dt = [&](int it, unsigned int dt) {
            if (it >= WINDOW) mbar_wait(BAR(0) + (it - WINDOW) * 8);
            int spin_it = 0;
#pragma unroll 1
            while ((int)(gtimer_lo() - due) < 0 && ++spin_it < SPIN_LIMIT) {}
            due += dt;
        };
        auto pace = [&](int it) { pace_dt(it, it < B_KV ? DT_F : (it < B_W1 ? DT_T : DT_T2)); };
        auto tile128 = [&](const CUtensorMap* m, int first, uint32_t dst, int k0) {
#pragma unroll 1
            for (int k = k0; k < 4; k++) {
                pace(first + k);
                tma2d(dst + k * 8192, m, hh * 128 + (k >> 1) * 64, jj * 128 + (k & 1) * 64, BAR(0) + (first + k) * 8, 8192, pol);
            }
        };
        tile128(&p.wq, B_WQ, sb + OFF_Y, 1);
        asm volatile("bar.sync 5, 320;" ::: "memory");
        tile128(&p.wuk, B_WUK, sb + OFF_X, 0);
        TS(61);
#pragma unroll 1
        for (int s = 0; s < 16; s++) {
            pace_dt(B_KV + s, s < 8 ? DT_F : DT_S);
            tma2d(sb + OFF_KV + s * 8192, &p.kv, (s & 7) * 64, bb * 4096 + chunk * 128 + (s >> 3) * 64, BAR(B_KV) + s * 8, 8192, pol);
        }
        const unsigned int t_poll = due + GATE_NS;
        if (lane == 0) sts32(MISC + 232, t_poll);
        TS(43);
        mbar_wait(BAR(B_YFREE));
#pragma unroll 1
        for (int k = 0; k < 2; k++) {
            pace(B_MOD + k);
            tma2d(sb + OFF_Z + k * 8192, &p.wmod, 1024 + 16 * i, k * 256, BAR(B_MOD) + k * 8, 8192, pol);
        }
        tile128(&p.wuv, B_WUV, sb + OFF_Y, 0);
        mbar_wait(BAR(B_XFREE));
#pragma unroll 1
        for (int k = 0; k < 4; k++) {
            pace(B_WO + k);
            tma3d(sb + OFF_X + k * 8192, &p.wo, 0, hh * 128 + jj * 32, k * 2, BAR(B_WO) + k * 8, 8192, pol);
        }
        {
            mbar_wait(BAR(B_EP));
            const unsigned int target = (lds32(MISC + 224) + 1u) * 32u;
            int it = 0;
#pragma unroll 1
            while ((int)(gtimer_lo() - t_poll) < 0 && ++it < SPIN_LIMIT) {}
            it = 0;
#pragma unroll 1
            while (!__all_sync(~0u, (int)(ld_cnt(&g_sync[(lane & 3) * 32 + 1]) - target) >= 0) && ++it < SPIN_LIMIT) {}
            if (lane == 0) mbar_arrive(BAR(B_G4));
            TS(13);
        }
        if (i < NFFN) {
            due = gtimer_lo();
            mbar_wait(BAR(B_ZFREE));
#pragma unroll 1
            for (int k = 0; k < 2; k++) {
                pace(B_W1 + k);
                tma2d(sb + OFF_Z + k * 8192, &p.w1, 16 * i, k * 256, BAR(B_W1) + k * 8, 8192, pol);
            }
            mbar_wait(BAR(B_KV0FREE));
#pragma unroll 1
            for (int k = 0; k < 2; k++) {
                pace(B_W2 + k);
                tma3d(sb + OFF_W2 + k * 8192, &p.w2, 0, 16 * i, k * 4, BAR(B_W2) + k * 8, 8192, pol);
            }
        }
        TS(40);
    } else if (warp == 9) {
        unsigned int ep = 0;
        if (lane == 0) {
            ep = ld_epoch(&g_sync[(i % NSYNC) * 32]);
            mbar_init(BAR(B_YFREE), 8);
            mbar_init(BAR(B_XFREE), 4);
            mbar_init(BAR(B_KV0FREE), 8);
            mbar_init(BAR(B_EP), 1);
            mbar_init(BAR(B_PEER0), 8);
            mbar_init(BAR(B_XCH), 1);
            mbar_init(BAR(B_G4), 1);
            mbar_init(BAR(B_XST), 2);
            mbar_expect_tx(BAR(B_XCH), 16384);
            mbar_expect_tx(BAR(B_XST), 128);
            asm volatile("fence.mbarrier_init.release.cluster;" ::: "memory");
        }
        __syncwarp();
        asm volatile("bar.arrive 5, 320;" ::: "memory");
        asm volatile("bar.arrive 4, 320;" ::: "memory");
        if (lane < 9) prefetch_map(&p.kv + lane);
        const uint4 z = make_uint4(0, 0, 0, 0);
        st128(&g_H[i * 32 + lane], z);
#pragma unroll
        for (int k = 0; k < 4; k++) st128(&g_Q[i * 128 + k * 32 + lane], z);
        uint32_t xr = 0;
        if (lane < 16) {
            const int V = i * 4 + (lane >> 2), e = lane & 3;
            const int m = (V >> 4) * 16 + ((V & 15) >> 1) + (e >> 1) * 8, b = (V & 1) * 2 + (e & 1);
            xr = ldnc16(p.x + b * 512 + m);
        }
        asm volatile("bar.sync 6, 288;" ::: "memory");
        __syncwarp();
        if (lane == 0) {
            sts32(MISC + 224, ep);
            sts32(MISC + 236, 0);
            mbar_arrive(BAR(B_EP));
        }
        mbar_wait(BAR(B_EP));
        ep = lds32(MISC + 224);
        const uint32_t tag = 1u + 2u * (ep & 1u);
        if (lane < 16) stsf(MISC + 32 + lane * 4, __uint_as_float(xr << 16));
        mbar_wait(BAR(B_P3));
        wait_cnt(&g_sync[(4 + (i & 3)) * 32 + 1], (ep + 1u) * 128u);
        __syncwarp();
        tma3d_mc(sb + OFF_X + rank * 16384, &p.qabs, 0, bb * 32, rank * 4, BAR(B_QABS), 32768);
        TS(41);
#pragma unroll 1
        for (int k = 0; k < 4; k++) st128(&g_C[i * 128 + k * 32 + lane], z);
        if (lane < 16) st128(&g_M[i * 16 + lane], z);
        {
            const uint32_t inv = ep & 1u;
            const uint4 zi = make_uint4(inv, 0, inv, 0);
            if (lane < 8) st128(reinterpret_cast<uint4*>(&g_X1[i * 16]) + lane, zi);
#pragma unroll 1
            for (int k = 0; k < 8; k++) {
                st128(reinterpret_cast<uint4*>(&g_O[i * 512]) + k * 32 + lane, zi);
                if (i < NFFN) st128(reinterpret_cast<uint4*>(&g_F[i * 512]) + k * 32 + lane, zi);
                spin(100);
            }
        }
        __syncwarp();
        if (lane == 0) mbar_arrive(BAR(B_CLR2));
        TS(44);
        mbar_wait_n(BAR(B_MOD), 2);
        float d[4] = {0.f, 0.f, 0.f, 0.f};
        gemv_512x16(d, sb + OFF_Z, sb + OFF_S, 0, 16, lane);
        __syncwarp();
        if (lane == 0) mbar_arrive(BAR(B_ZFREE));
        if ((lane & 3) < 2) put4(&g_M[i * 16 + (lane >> 2) * 2 + (lane & 3)], d[0], d[1], d[2], d[3], tag);
        __syncwarp();
        if (lane == 0 && i >= 32 && i < 96) red_cnt(&g_sync[4 * 32 + 2]);
        TS(42);
        {
            const float4 v = get4(&g_M[((lane >> 2) & 1) * 3 * 512 + i * 4 + (lane & 3)], lane < 8, tag);
            if (lane < 8) stsf4(MISC + 96 + lane * 16, v);
        }
        __syncwarp();
        if (lane == 0) {
            if (i < NFFN) {
                wait_cnt(&g_sync[4 * 32 + 2], (ep + 1u) * 64u);
                mbar_wait(BAR(B_KV0FREE));
                asm volatile("fence.proxy.async.global;" ::: "memory");
                mbar_expect_tx(BAR(B_MODV), 16384);
                asm volatile("cp.async.bulk.shared::cluster.global.mbarrier::complete_tx::bytes [%0], [%1], %2, [%3];"
                             ::"r"(sb + OFF_SBCB), "l"(&g_M[512]), "r"(16384), "r"(BAR(B_MODV)) : "memory");
            } else {
                mbar_arrive(BAR(B_MODV));
            }
            TS(45);
        }
    } else {
        const uint32_t ACT = sb + OFF_ACT, ACTB = sb + OFF_ACT + 1152, RED = sb + OFF_RED;
        const int g = lane >> 2, q = lane & 3;
        const int vrr = (lane & 15) >> 1, vb0 = (lane & 1) * 2;
        uint32_t cw[4];
        uint4 xv[2];
        uint32_t xh[4];
        {
            const uint4* xp = reinterpret_cast<const uint4*>(p.x + (warp & 3) * 512 + lane * 16);
            xv[0] = ldnc128_if(xp, warp < 4);
            xv[1] = ldnc128_if(xp + 1, warp < 4);
            const __nv_bfloat16* xq = p.x + vb0 * 512 + jj * 128 + warp * 16 + vrr;
            xh[0] = ldnc16(xq); xh[1] = ldnc16(xq + 512); xh[2] = ldnc16(xq + 8); xh[3] = ldnc16(xq + 520);
        }
#pragma unroll
        for (int b = 0; b < 4; b++) cw[b] = ldnc32(p.c + b * 512 + 2 * t);
        if (lane == 0) {
#pragma unroll
            for (int k = 0; k < 5; k++) {
                int idx = 4 + warp * 5 + k;
                if (idx >= B_YFREE) idx = (idx == 39) ? B_ZFREE : (idx == 40 ? B_P3 : (idx == 41 ? B_CLR2 : B_MODV));
                mbar_init(BAR(0) + idx * 8, 1);
            }
            asm volatile("fence.mbarrier_init.release.cluster;" ::: "memory");
        }
        __syncwarp();
        asm volatile("bar.arrive 5, 320;" ::: "memory");
        asm volatile("bar.arrive 6, 288;" ::: "memory");
        asm volatile("bar.sync 4, 320;" ::: "memory");

#pragma unroll
        for (int b = 0; b < 4; b++) {
            const float c0 = bf_lo(cw[b]), c1 = bf_hi(cw[b]);
            sts32(sb + OFF_S + b * 1040 + t * 4, pack_bf16(__fdividef(c0, 1.f + __expf(-c0)), __fdividef(c1, 1.f + __expf(-c1))));
        }
        if (warp < 4) {
            const uint32_t u[8] = {xv[0].x, xv[0].y, xv[0].z, xv[0].w, xv[1].x, xv[1].y, xv[1].z, xv[1].w};
            float s = 0.f, ss = 0.f;
#pragma unroll
            for (int k = 0; k < 8; k++) s += bf_lo(u[k]) + bf_hi(u[k]);
#pragma unroll
            for (int o = 16; o; o >>= 1) s += __shfl_xor_sync(~0u, s, o);
            const float mean = s * (1.f / 512.f);
#pragma unroll
            for (int k = 0; k < 8; k++) { const float d0 = bf_lo(u[k]) - mean, d1 = bf_hi(u[k]) - mean; ss += d0 * d0 + d1 * d1; }
#pragma unroll
            for (int o = 16; o; o >>= 1) ss += __shfl_xor_sync(~0u, ss, o);
            if (lane == 0) { stsf(MISC + warp * 8, mean); stsf(MISC + warp * 8 + 4, rsqrtf(ss * (1.f / 512.f) + 1e-5f)); }
        }
        bar_main();
        mbar_wait(BAR(B_EP));
        const unsigned int ep = lds32(MISC + 224);
        const uint32_t tag = 1u + 2u * (ep & 1u);
        const uint32_t par = (ep & 1u) ^ 1u;
        if (warp < 2) {
            mbar_wait(BAR(B_WA));
            TS0(26);
            float d[4] = {0.f, 0.f, 0.f, 0.f};
            gemv_512x16(d, sb + OFF_Z + warp * 4096 - jj * 4096, sb + OFF_S, jj * 128, 4, lane);
            if (q < 2) put4(&g_H[i * 32 + warp * 16 + g * 2 + q], d[0], d[1], d[2], d[3], tag);
        }
        TS0(1);
        mbar_wait_n(BAR(B_WQ), 4);
        uint32_t afr[8][4];
        gemv_y_load(afr);
        TS0(3);
        {
            const float4 a = get4sum4(&g_H[(4 * (8 * jj + warp)) * 32 + lane], 32, tag);
            const float cx = __shfl_down_sync(~0u, a.x, 16), cy = __shfl_down_sync(~0u, a.y, 16);
            const float cz = __shfl_down_sync(~0u, a.z, 16), cwv = __shfl_down_sync(~0u, a.w, 16);
            if (lane < 16) {
                const float2 s0 = ldsf2(MISC + vb0 * 8), s1 = ldsf2(MISC + vb0 * 8 + 8);
                sts_frag(ACT, 272, warp * 16 + vrr, vb0,
                         (__uint_as_float(xh[0] << 16) - s0.x) * s0.y * (1.f + cx) + a.x,
                         (__uint_as_float(xh[1] << 16) - s1.x) * s1.y * (1.f + cy) + a.y,
                         (__uint_as_float(xh[2] << 16) - s0.x) * s0.y * (1.f + cz) + a.z,
                         (__uint_as_float(xh[3] << 16) - s1.x) * s1.y * (1.f + cwv) + a.w);
            }
        }
        bar_main();
        TS0(2);
        gemv_y_put(afr, &g_Q[i * 128], ACT, tag);
        __syncwarp();
        if (lane == 0) mbar_arrive(BAR(B_YFREE));
        mbar_wait_n(BAR(B_WUK), 4);
        TS0(5);
        if (warp < 4) {
            const float4 a = get4sum4(&g_Q[hh * 4 * 128 + t], 128, tag);
            sts_frag(ACTB, 272, (t >> 4) * 16 + vrr, vb0, a.x, a.y, a.z, a.w);
        }
        bar_main();
        TS0(4);
        {
            float d[4] = {0.f, 0.f, 0.f, 0.f};
            const int blk = lane >> 3, r8 = lane & 7;
            const uint32_t arow = sb + OFF_X + (warp * 16 + (blk & 1) * 8 + r8) * 128;
            const uint32_t brow = ACTB + (r8 & 3) * 272 + blk * 16;
            uint32_t a[8][4], b[4][4];
#pragma unroll
            for (int k = 0; k < 8; k++) ldsm4(a[k], arow + (k >> 2) * 16384 + ((((k & 3) * 2 + (blk >> 1)) ^ r8) << 4));
#pragma unroll
            for (int k = 0; k < 4; k++) ldsm4(b[k], brow + k * 64);
            float e[4] = {0.f, 0.f, 0.f, 0.f};
#pragma unroll
            for (int k = 0; k < 4; k++) {
                mma16816(d, a[2 * k], b[k][0], b[k][1]);
                mma16816(e, a[2 * k + 1], b[k][2], b[k][3]);
            }
            d[0] += e[0]; d[1] += e[1]; d[2] += e[2]; d[3] += e[3];
            const float sc = 0.08838834764831845f * 1.4426950408889634f;
            if (q < 2) sts_frag(RED, 256, warp * 16 + g, 2 * q, d[0] * sc, d[1] * sc, d[2] * sc, d[3] * sc);
            fence_async_smem();
            bar_main();
            if (t == 0) {
#pragma unroll 1
                for (int b = 0; b < 4; b++) bulk_s2g(&g_qabs[(b * 32 + hh) * 512 + jj * 128], RED + b * 256, 256);
                asm volatile("cp.async.bulk.commit_group;" ::: "memory");
                asm volatile("cp.async.bulk.wait_group 0;" ::: "memory");
#pragma unroll
                for (int r = 0; r < 4; r++) red_cnt(&g_sync[(4 + r) * 32 + 1]);
                mbar_arrive(BAR(B_P3));
            }
            TS0(6);
        }
        const int wg = warp >> 2, wq = warp & 3;
        {
            const uint32_t MX = RED;
            const uint32_t LRED = RED + 512;
            const uint32_t OST = ACTB + 128, PST = ACTB;
            const uint32_t ALPHA = RED + 1536, MRUN = RED + 1664;
            float o[4][16];
            float lsum[8];
#pragma unroll
            for (int k = 0; k < 8; k++) lsum[k] = 0.f;
            if (t < 32) stsf(MRUN + t * 4, -INFINITY);
            mbar_wait(BAR(B_QABS));
            TS0(7);
            float s[16];
            auto qk = [&](int c0, int c1) {
                uint32_t da = desc_lo(SB0 + OFF_KV) + wg * (65536 >> 4) + c0 * (8192 >> 4), db = desc_lo(SB0 + OFF_X) + c0 * (4096 >> 4);
#pragma unroll 1
                for (int cb = c0; cb < c1; cb++) {
                    mbar_wait(BAR(B_KV) + (wg * 8 + cb) * 8);
                    wg_fence();
#pragma unroll
                    for (int k = 0; k < 4; k++) wgmma_n32<0>(s, da + k * 2, db + k * 2, (cb | k) != 0);
                    wg_commit();
                    da += 8192 >> 4;
                    db += 4096 >> 4;
                }
            };
            if (wg == 1) qk(0, QK_EARLY);
#pragma unroll 1
            for (int tile = 0; tile < 2; tile++) {
                if (wg == tile) {
                    qk(tile == 0 ? 0 : QK_EARLY, 8);
                    wg_wait0();
                    reg_fence(s);
                    if (tile == 1) {
                        __syncwarp();
                        if (lane == 0) {
                            mbar_arrive(BAR(B_XFREE));
                            mbar_arrive(BAR(B_KV0FREE));
                            asm volatile("mbarrier.arrive.relaxed.cluster.shared::cluster.b64 _, [%0];" ::"r"(mapa(BAR(B_PEER0), rank ^ 1)) : "memory");
                        }
                    }
                    if (wq == 0) TS(8 + tile * 2);
                    float m[8];
#pragma unroll
                    for (int jb = 0; jb < 4; jb++) {
                        m[2 * jb] = fmaxf(s[4 * jb], s[4 * jb + 2]);
                        m[2 * jb + 1] = fmaxf(s[4 * jb + 1], s[4 * jb + 3]);
                    }
                    {
                        const bool u4 = lane & 16, u3 = lane & 8, u2 = lane & 4;
                        float h4[4], h2[2];
#pragma unroll
                        for (int k = 0; k < 4; k++) h4[k] = fmaxf(u4 ? m[k + 4] : m[k], __shfl_xor_sync(~0u, u4 ? m[k] : m[k + 4], 16));
#pragma unroll
                        for (int k = 0; k < 2; k++) h2[k] = fmaxf(u3 ? h4[k + 2] : h4[k], __shfl_xor_sync(~0u, u3 ? h4[k] : h4[k + 2], 8));
                        const float h1 = fmaxf(u2 ? h2[1] : h2[0], __shfl_xor_sync(~0u, u2 ? h2[0] : h2[1], 4));
                        stsf(MX + (wq * 32 + 8 * (g >> 1) + 2 * q + (g & 1)) * 4, h1);
                    }
                    if (tile == 0) asm volatile("bar.sync 2, 128;" ::: "memory"); else asm volatile("bar.sync 3, 128;" ::: "memory");
                    const float mold = ldsf(MRUN + tile * 128 + lane * 4);
                    const float mnew = fmaxf(fmaxf(fmaxf(ldsf(MX + lane * 4), ldsf(MX + 128 + lane * 4)), fmaxf(ldsf(MX + 256 + lane * 4), ldsf(MX + 384 + lane * 4))), mold);
                    uint32_t lo[4], hi[4];
#pragma unroll
                    for (int jb = 0; jb < 4; jb++) {
                        const float m0 = __shfl_sync(~0u, mnew, 8 * jb + 2 * q), m1 = __shfl_sync(~0u, mnew, 8 * jb + 2 * q + 1);
                        lo[jb] = pack_bf16(ex2(s[4 * jb] - m0), ex2(s[4 * jb + 1] - m1));
                        hi[jb] = pack_bf16(ex2(s[4 * jb + 2] - m0), ex2(s[4 * jb + 3] - m1));
                        lsum[2 * jb] = bf_lo(lo[jb]) + bf_lo(hi[jb]);
                        lsum[2 * jb + 1] = bf_hi(lo[jb]) + bf_hi(hi[jb]);
                    }
                    const uint32_t prow = sb + OFF_P + tile * 4096 + ((lane + 16 * rank) & 31) * 128;
                    stsm4t(prow + (((2 * wq) ^ (lane & 7)) << 4), lo[0], lo[1], lo[2], lo[3]);
                    stsm4t(prow + (((2 * wq + 1) ^ (lane & 7)) << 4), hi[0], hi[1], hi[2], hi[3]);
                    fence_async_smem();
                    if (wq == 0) { stsf(ALPHA + lane * 4, ex2(mold - mnew)); stsf(MRUN + (tile + 1) * 128 + lane * 4, mnew); }
                }
                bar_main();
                TS0(27 + tile);
                if (tile == 1) {
                    wg_wait0();
#pragma unroll
                    for (int mt = 0; mt < 4; mt++) reg_fence(o[mt]);
#pragma unroll
                    for (int jb = 0; jb < 4; jb++) {
                        const float2 a = ldsf2(ALPHA + ((8 * jb + 2 * q + 16 * rank) & 31) * 4);
#pragma unroll
                        for (int mt = 0; mt < 4; mt++) { o[mt][4 * jb] *= a.x; o[mt][4 * jb + 1] *= a.y; o[mt][4 * jb + 2] *= a.x; o[mt][4 * jb + 3] *= a.y; }
                    }
                }
                {
                    const uint32_t da = desc_lo(SB0 + OFF_KV) + tile * (65536 >> 4) + wg * (32768 >> 4), db = desc_lo(SB0 + OFF_P) + tile * (4096 >> 4);
                    wg_fence();
#pragma unroll
                    for (int mt = 0; mt < 4; mt++) {
#pragma unroll
                        for (int k = 0; k < 4; k++)
                            wgmma_n32<1>(o[mt], da + mt * (8192 >> 4) + k * (2048 >> 4), db + k * 2, tile | k);
                        wg_commit();
                    }
                }
                if (wg == tile) {
#pragma unroll
                    for (int of = 4; of <= 16; of <<= 1) {
#pragma unroll
                        for (int k = 0; k < 8; k++) lsum[k] += __shfl_xor_sync(~0u, lsum[k], of);
                    }
                    if (g == 0) {
#pragma unroll
                        for (int jb = 0; jb < 4; jb++)
                            asm volatile("st.shared.v2.f32 [%0], {%1,%2};" ::"r"(LRED + (warp * 32 + 8 * jb + 2 * q) * 4), "f"(lsum[2 * jb]), "f"(lsum[2 * jb + 1]) : "memory");
                    }
                    if (tile == 1) {
                        asm volatile("bar.sync 3, 128;" ::: "memory");
                        if (wq == 0) {
                            float l0 = 0.f, l1 = 0.f;
#pragma unroll
                            for (int w = 0; w < 4; w++) { l0 += ldsf(LRED + (w * 32 + lane) * 4); l1 += ldsf(LRED + ((w + 4) * 32 + lane) * 4); }
                            const float l = l0 * ldsf(ALPHA + lane * 4) + l1;
                            const float mf = ldsf(MRUN + 256 + lane * 4);
                            if ((lane >> 4) == (int)rank) {
                                asm volatile("st.shared.v2.f32 [%0], {%1,%2};" ::"r"(OST + (lane & 15) * 8), "f"(mf), "f"(l) : "memory");
                            } else {
                                mbar_wait(BAR(B_PEER0));
                                st_async2(mapa(PST + (lane & 15) * 8, rank ^ 1), mf, l, mapa(BAR(B_XST), rank ^ 1));
                            }
                            __syncwarp();
                            if (lane == 0) mbar_arrive(BAR(B_XST));
                        }
                    }
                }
                if (tile == 0 && wg == 0) {
                    wg_wait0();
                    __syncwarp();
                    if (lane == 0) {
                        mbar_arrive(BAR(B_KV0FREE));
                        asm volatile("mbarrier.arrive.relaxed.cluster.shared::cluster.b64 _, [%0];" ::"r"(mapa(BAR(B_PEER0), rank ^ 1)) : "memory");
                    }
                    TS0(9);
                }
            }
            mbar_wait(BAR(B_PEER0));
            {
                const uint32_t rx = mapa(sb + OFF_XCH + t * 16, rank ^ 1), rb = mapa(BAR(B_XCH), rank ^ 1);
                asm volatile("wgmma.wait_group.sync.aligned 3;" ::: "memory");
                reg_fence(o[0]);
                st_async4(rx, pack_bf16(o[0][8], o[0][9]), pack_bf16(o[0][10], o[0][11]), pack_bf16(o[0][12], o[0][13]), pack_bf16(o[0][14], o[0][15]), rb);
                asm volatile("wgmma.wait_group.sync.aligned 2;" ::: "memory");
                reg_fence(o[1]);
                st_async4(rx + 4096, pack_bf16(o[1][8], o[1][9]), pack_bf16(o[1][10], o[1][11]), pack_bf16(o[1][12], o[1][13]), pack_bf16(o[1][14], o[1][15]), rb);
                asm volatile("wgmma.wait_group.sync.aligned 1;" ::: "memory");
                reg_fence(o[2]);
                st_async4(rx + 8192, pack_bf16(o[2][8], o[2][9]), pack_bf16(o[2][10], o[2][11]), pack_bf16(o[2][12], o[2][13]), pack_bf16(o[2][14], o[2][15]), rb);
                wg_wait0();
                reg_fence(o[3]);
                st_async4(rx + 12288, pack_bf16(o[3][8], o[3][9]), pack_bf16(o[3][10], o[3][11]), pack_bf16(o[3][12], o[3][13]), pack_bf16(o[3][14], o[3][15]), rb);
            }
            TS0(11);
            mbar_wait(BAR(B_XST));
            float ca[4], cb[4];
#pragma unroll
            for (int k = 0; k < 4; k++) {
                const int n = 8 * (k >> 1) + 2 * q + (k & 1);
                const float2 so = ldsf2(OST + n * 8), sp = ldsf2(PST + n * 8);
                const float mx = fmaxf(so.x, sp.x);
                ca[k] = ex2(so.x - mx);
                cb[k] = ex2(sp.x - mx);
            }
#pragma unroll
            for (int mt = 0; mt < 4; mt++) {
                o[mt][0] *= ca[0]; o[mt][1] *= ca[1]; o[mt][2] *= ca[0]; o[mt][3] *= ca[1];
                o[mt][4] *= ca[2]; o[mt][5] *= ca[3]; o[mt][6] *= ca[2]; o[mt][7] *= ca[3];
            }
            if (warp == 0) {
                const float2 so = ldsf2(OST + (lane & 15) * 8), sp = ldsf2(PST + (lane & 15) * 8);
                const float mx = fmaxf(so.x, sp.x);
                const float l = so.y * ex2(so.x - mx) + sp.y * ex2(sp.x - mx);
                const float ln = __shfl_down_sync(~0u, l, 1), mn = __shfl_down_sync(~0u, mx, 1);
                if (lane < 16 && (lane & 1) == 0) put4(&g_stat[((rank * 4 + (lane >> 2)) * 64 + (i >> 1)) * 2 + ((lane >> 1) & 1)], mx, l, mn, ln, tag);
            }
            const uint32_t keep = (g == 0) ? 0xFFFEFFFEu : 0xFFFFFFFFu;
            const uint32_t tg = (g == 0) ? ((ep & 1u) ? 0u : 0x00010001u) : 0u;
            const int hl = lane & 15, mi2 = lane >> 4;
            mbar_wait(BAR(B_XCH));
            TS0(46);
#pragma unroll
            for (int mt = 0; mt < 4; mt++) {
                const uint4 r = lds128(sb + OFF_XCH + mt * 4096 + t * 16);
                const uint32_t lo0 = (pack_bf16(o[mt][0] + cb[0] * bf_lo(r.x), o[mt][1] + cb[1] * bf_hi(r.x)) & keep) | tg;
                const uint32_t hi0 = (pack_bf16(o[mt][2] + cb[0] * bf_lo(r.y), o[mt][3] + cb[1] * bf_hi(r.y)) & keep) | tg;
                const uint32_t lo1 = (pack_bf16(o[mt][4] + cb[2] * bf_lo(r.z), o[mt][5] + cb[3] * bf_hi(r.z)) & keep) | tg;
                const uint32_t hi1 = (pack_bf16(o[mt][6] + cb[2] * bf_lo(r.w), o[mt][7] + cb[3] * bf_hi(r.w)) & keep) | tg;
                const uint32_t row = sb + OFF_STG + (wg * 2 + (mt >> 1)) * 4096 + hl * 256;
                const int ch = (mt & 1) * 8 + wq * 2 + mi2;
                stsm4t(row + ((ch ^ (hl & 7)) << 4), lo0, lo1, hi0, hi1);
            }
            fence_async_smem();
            if (wg == 0) asm volatile("bar.sync 2, 128;" ::: "memory"); else asm volatile("bar.sync 3, 128;" ::: "memory");
            if (warp == 4) TS(47);
            if (wq == 0 && lane == 0) {
                bulk_s2g(&g_part[i * 1024 + wg * 512], sb + OFF_STG + wg * 8192, 8192);
                asm volatile("cp.async.bulk.commit_group;" ::: "memory");
                asm volatile("cp.async.bulk.wait_group 0;" ::: "memory");
                if (atomicAdd(reinterpret_cast<unsigned int*>(smem + OFF_MISC + 236), 1u) == 1u) red_cnt(&g_sync[bb * 32 + 1]);
            }
            TS0(12);
        }
        mbar_wait(BAR(B_CLR2));
        const uint32_t SCR = sb + OFF_SCR;
        {
            const int b = warp >> 1;
            const uint32_t ptag = par;
            const int pi = lane >> 3, v = (warp & 1) * 8 + (lane & 7);
            const uint4* sp = &g_stat[((hh >> 2) * 64 + b * 16 + (lane & 15)) * 2 + ((hh >> 1) & 1)];
            const uint4* src = &g_part[(2 * (b * 16 + pi) + (hh >> 4)) * 1024 + (jj * 16 + (hh & 15)) * 16 + v];
            float acc[8];
            int it = 0;
            bool ok;
            mbar_wait_n(BAR(B_WUV), 4);
            gemv_y_load(afr);
            float wi;
            {
                const unsigned int t_stat = lds32(MISC + 232) - STAT_LEAD;
#pragma unroll 1
                while ((int)(gtimer_lo() - t_stat) < 0 && ++it < SPIN_LIMIT) {}
                const float4 su = get4(sp, true, tag);
                const float mi = (hh & 1) ? su.z : su.x, li = (hh & 1) ? su.w : su.y;
                float mx = mi;
#pragma unroll
                for (int of = 8; of; of >>= 1) mx = fmaxf(mx, __shfl_xor_sync(~0u, mx, of));
                wi = ex2(mi - mx);
                float L = wi * li;
#pragma unroll
                for (int of = 8; of; of >>= 1) L += __shfl_xor_sync(~0u, L, of);
                wi = __fdividef(wi, L);
            }
            float w4[4];
#pragma unroll
            for (int k = 0; k < 4; k++) w4[k] = __shfl_sync(~0u, wi, 4 * k + pi);
            mbar_wait(BAR(B_G4));
            it = 0;
#pragma unroll 1
            do {
                uint4 r[4];
#pragma unroll
                for (int k = 0; k < 4; k++) r[k] = ld128(src + (size_t)k * 8 * 1024);
                ok = true;
#pragma unroll
                for (int k = 0; k < 8; k++) acc[k] = 0.f;
#pragma unroll
                for (int k = 0; k < 4; k++) {
                    const float w = w4[k];
                    ok = ok & ((r[k].x & 1u) == ptag);
                    acc[0] += w * bf_lo(r[k].x); acc[1] += w * bf_hi(r[k].x);
                    acc[2] += w * bf_lo(r[k].y); acc[3] += w * bf_hi(r[k].y);
                    acc[4] += w * bf_lo(r[k].z); acc[5] += w * bf_hi(r[k].z);
                    acc[6] += w * bf_lo(r[k].w); acc[7] += w * bf_hi(r[k].w);
                }
            } while (!__all_sync(~0u, ok) && ++it < SPIN_LIMIT);
            {
                const bool u4 = lane & 16, u3 = lane & 8;
                float h4[4], h2[2];
#pragma unroll
                for (int k = 0; k < 4; k++) h4[k] = (u4 ? acc[k + 4] : acc[k]) + __shfl_xor_sync(~0u, u4 ? acc[k] : acc[k + 4], 16);
#pragma unroll
                for (int k = 0; k < 2; k++) h2[k] = (u3 ? h4[k + 2] : h4[k]) + __shfl_xor_sync(~0u, u3 ? h4[k] : h4[k + 2], 8);
                const int ch = v ^ (hh & 7);
                sts32(ACT + b * 272 + (ch * 8 + (u4 ? 4 : 0) + (u3 ? 2 : 0)) * 2, pack_bf16(h2[0], h2[1]));
            }
            bar_main();
            TS0(14);
        }
        gemv_y_put(afr, &g_C[i * 128], ACT, tag);
        TS0(17);
        mbar_wait_n(BAR(B_WO), 4);
        {
            const int blk = lane >> 3, r8 = lane & 7;
            const uint32_t wb = sb + OFF_X + warp * 4096 + ((blk >> 1) * 8 + r8) * 128;
#pragma unroll
            for (int mt = 0; mt < 4; mt++) {
                const uint32_t co = ((2 * mt + (blk & 1)) ^ r8) << 4;
                ldsm4t(afr[2 * mt], wb + co);
                ldsm4t(afr[2 * mt + 1], wb + 16 * 128 + co);
            }
        }
        if (warp == 0) {
            const float4 a = get4sum4(&g_C[hh * 4 * 128 + jj * 32 + lane], 128, tag);
            sts_frag(ACTB, 80, (t >> 4) * 16 + vrr, vb0, a.x, a.y, a.z, a.w);
        }
        bar_main();
        TS0(16);
        {
            uint32_t b[4];
            ldsm4(b, ACTB + (lane & 3) * 80 + (lane >> 3) * 16);
            uint32_t px[4], py[4];
#pragma unroll
            for (int mt = 0; mt < 4; mt++) {
                float d[4] = {0.f, 0.f, 0.f, 0.f};
                mma16816(d, afr[2 * mt], b[0], b[1]);
                mma16816(d, afr[2 * mt + 1], b[2], b[3]);
                px[mt] = (pack_bf16(d[0], d[1]) & ~1u) | par;
                py[mt] = pack_bf16(d[2], d[3]);
            }
            if (q < 2) {
                uint2* dst = &g_O[i * 512 + warp * 64 + g * 2 + q];
#pragma unroll
                for (int mt = 0; mt < 4; mt++) st64(dst + mt * 16, px[mt], py[mt]);
            }
            TS0(18);
        }
        const int V = i * 4 + (t & 3);
        const int vm = (V >> 4) * 16 + ((V & 15) >> 1), vb = (V & 1) * 2;
        float4 x1 = make_float4(0.f, 0.f, 0.f, 0.f);
        {
            mbar_wait(BAR(B_MODV));
            const float4 r = reduce16(g_O, 128, par, G6ADELAY);
            if (t < 4) {
                const float4 x0 = ldsf4(MISC + 32 + t * 16), ga = ldsf4(MISC + 96 + t * 16);
                x1 = make_float4(x0.x + ga.x * r.x, x0.y + ga.y * r.y, x0.z + ga.z * r.z, x0.w + ga.w * r.w);
                put2(&g_X1[i * 16 + t], x1.x, x1.y, x1.z, x1.w, par);
            }
            TS0(19);
        }
        if (i < NFFN) {
            float4 mv[4];
#pragma unroll
            for (int k = 0; k < 4; k++) {
                uint4 u = lds128(sb + OFF_SBCB + (t + 256 * k) * 16);
                int it = 0;
                while ((u.x & 3u) != tag && ++it < SPIN_LIMIT) u = ld128(&g_M[512 + t + 256 * k]);
                mv[k] = as_f4(u);
            }
            mbar_wait_n(BAR(B_W1), 4);
            {
                const int blk = lane >> 3, r8 = lane & 7;
                const uint32_t w1r = sb + OFF_Z + (warp * 64 + (blk >> 1) * 8 + r8) * 32 + (((blk & 1) ^ ((r8 >> 2) & 1)) << 4);
                const uint32_t w2r = sb + OFF_W2 + warp * 2048 + ((blk >> 1) * 8 + r8) * 128;
#pragma unroll
                for (int k = 0; k < 4; k++) {
                    ldsm4t(afr[k], w1r + k * 512);
                    ldsm4t(afr[4 + k], w2r + (((2 * k + (blk & 1)) ^ r8) << 4));
                }
            }
            TS0(21);
            uint2 ua, ub;
            {
                int it = 0;
#pragma unroll 1
                do { ua = ld64(&g_X1[(t >> 2) * 16 + (t & 3)]); ub = ld64(&g_X1[(t >> 2) * 16 + (t & 3) + 1024]); } while (!__all_sync(~0u, (((ua.x ^ par) | (ub.x ^ par)) & 1u) == 0) && ++it < SPIN_LIMIT);
            }
            const float4 a = as_f4(ua), b = as_f4(ub);
            float s0 = (a.x + a.z) + (b.x + b.z), s1 = (a.y + a.w) + (b.y + b.w);
            float q0 = (a.x * a.x + a.z * a.z) + (b.x * b.x + b.z * b.z), q1 = (a.y * a.y + a.w * a.w) + (b.y * b.y + b.w * b.w);
#pragma unroll
            for (int of = 2; of <= 16; of <<= 1) {
                s0 += __shfl_xor_sync(~0u, s0, of); s1 += __shfl_xor_sync(~0u, s1, of);
                q0 += __shfl_xor_sync(~0u, q0, of); q1 += __shfl_xor_sync(~0u, q1, of);
            }
            const uint32_t ST = SCR + 1024, ACT2 = SCR + 4096;
            if (lane < 2) stsf4(ST + (warp * 2 + lane) * 16, make_float4(s0, q0, s1, q1));
            bar_main();
            TS0(20);
            float4 tot = make_float4(0.f, 0.f, 0.f, 0.f);
#pragma unroll
            for (int w = 0; w < 8; w++) add4(tot, ldsf4(ST + (w * 2 + (t & 1)) * 16));
            const float mean0 = tot.x * (1.f / 512.f), mean1 = tot.z * (1.f / 512.f);
            const float r0 = rsqrtf(fmaxf(tot.y * (1.f / 512.f) - mean0 * mean0, 0.f) + 1e-5f);
            const float r1 = rsqrtf(fmaxf(tot.w * (1.f / 512.f) - mean1 * mean1, 0.f) + 1e-5f);
            const int m0 = (t >> 4) * 16 + vrr;
            sts_frag(ACT2, 1040, m0, vb0, (a.x - mean0) * r0 * (1.f + mv[2].x) + mv[0].x, (a.y - mean1) * r1 * (1.f + mv[2].y) + mv[0].y,
                     (a.z - mean0) * r0 * (1.f + mv[2].z) + mv[0].z, (a.w - mean1) * r1 * (1.f + mv[2].w) + mv[0].w);
            sts_frag(ACT2, 1040, m0 + 256, vb0, (b.x - mean0) * r0 * (1.f + mv[3].x) + mv[1].x, (b.y - mean1) * r1 * (1.f + mv[3].y) + mv[1].y,
                     (b.z - mean0) * r0 * (1.f + mv[3].z) + mv[1].z, (b.w - mean1) * r1 * (1.f + mv[3].w) + mv[1].w);
            bar_main();
            float d[4] = {0.f, 0.f, 0.f, 0.f};
            {
                const uint32_t brow = ACT2 + (lane & 3) * 1040 + (warp * 64 + (lane >> 3) * 8) * 2;
                uint32_t b0[4], b1[4];
                ldsm4(b0, brow);
                ldsm4(b1, brow + 64);
                float e[4] = {0.f, 0.f, 0.f, 0.f};
                mma16816(d, afr[0], b0[0], b0[1]);
                mma16816(e, afr[1], b0[2], b0[3]);
                mma16816(d, afr[2], b1[0], b1[1]);
                mma16816(e, afr[3], b1[2], b1[3]);
                d[0] += e[0]; d[1] += e[1]; d[2] += e[2]; d[3] += e[3];
            }
            const uint32_t HR = SCR + 2048;
            if (q < 2) {
                const uint32_t a0 = HR + (warp * 64 + (2 * q) * 16 + (g >> 1) * 4 + (g & 1)) * 4;
                stsf(a0, d[0]); stsf(a0 + 64, d[1]); stsf(a0 + 8, d[2]); stsf(a0 + 72, d[3]);
            }
            bar_main();
            float4 hs = ldsf4(HR + ((g & 3) * 16 + q * 4) * 4);
#pragma unroll
            for (int w = 1; w < 8; w++) add4(hs, ldsf4(HR + (w * 64 + (g & 3) * 16 + q * 4) * 4));
            const uint32_t b0r = pack_bf16(fmaxf(hs.x, 0.f), fmaxf(hs.y, 0.f)), b1r = pack_bf16(fmaxf(hs.z, 0.f), fmaxf(hs.w, 0.f));
            TS0(22);
            uint32_t px[4], py[4];
#pragma unroll
            for (int mt = 0; mt < 4; mt++) {
                float e[4] = {0.f, 0.f, 0.f, 0.f};
                mma16816(e, afr[4 + mt], b0r, b1r);
                px[mt] = (pack_bf16(e[0], e[1]) & ~1u) | par;
                py[mt] = pack_bf16(e[2], e[3]);
            }
            if (q < 2) {
                uint2* dst = &g_F[i * 512 + warp * 64 + g * 2 + q];
#pragma unroll
                for (int mt = 0; mt < 4; mt++) st64(dst + mt * 16, px[mt], py[mt]);
            }
            TS0(23);
        }
        {
            const float4 r = reduce16(g_F, NFFN, par, i < NFFN ? HOPDELAY : FFNDELAY);
            if (t < 4) {
                const float4 gb = ldsf4(MISC + 96 + 64 + t * 16);
                p.out[vb * 512 + vm] = __float2bfloat16_rn(x1.x + gb.x * r.x);
                p.out[(vb + 1) * 512 + vm] = __float2bfloat16_rn(x1.y + gb.y * r.y);
                p.out[vb * 512 + vm + 8] = __float2bfloat16_rn(x1.z + gb.z * r.z);
                p.out[(vb + 1) * 512 + vm + 8] = __float2bfloat16_rn(x1.w + gb.w * r.w);
            }
            if (i == 0 && t < NSYNC) g_sync[t * 32] = ep + 1u;
            TS0(24);
        }
    }
}

typedef CUresult (*EncodeFn)(CUtensorMap*, CUtensorMapDataType, cuuint32_t, void*, const cuuint64_t*, const cuuint64_t*, const cuuint32_t*,
                             const cuuint32_t*, CUtensorMapInterleave, CUtensorMapSwizzle, CUtensorMapL2promotion, CUtensorMapFloatOOBfill);

void make_map(EncodeFn enc, CUtensorMap* m, const void* base, int rank, const cuuint64_t* dims, const cuuint64_t* strides, const cuuint32_t* box,
              CUtensorMapSwizzle sw) {
    cuuint32_t es[3] = {1, 1, 1};
    CUresult r = enc(m, CU_TENSOR_MAP_DATA_TYPE_BFLOAT16, rank, const_cast<void*>(base), dims, strides, box, es, CU_TENSOR_MAP_INTERLEAVE_NONE, sw,
                     CU_TENSOR_MAP_L2_PROMOTION_NONE, CU_TENSOR_MAP_FLOAT_OOB_FILL_NONE);
    if (r != CUDA_SUCCESS) fprintf(stderr, "cuTensorMapEncodeTiled failed: %d\n", (int)r);
}
void map2d(EncodeFn enc, CUtensorMap* m, const void* base, uint64_t rows, uint64_t cols, uint32_t boxr, uint32_t boxc, CUtensorMapSwizzle sw) {
    cuuint64_t dims[2] = {cols, rows};
    cuuint64_t strides[1] = {cols * 2};
    cuuint32_t box[2] = {boxc, boxr};
    make_map(enc, m, base, 2, dims, strides, box, sw);
}
void map3d(EncodeFn enc, CUtensorMap* m, const void* base, uint64_t rows, uint32_t boxr, uint32_t boxb) {
    cuuint64_t dims[3] = {64, rows, 8};
    cuuint64_t strides[2] = {1024, 128};
    cuuint32_t box[3] = {64, boxr, boxb};
    make_map(enc, m, base, 3, dims, strides, box, CU_TENSOR_MAP_SWIZZLE_128B);
}

}

extern "C" void kernel_launch(void* const* d_in, const int* in_sizes, int n_in, void* d_out, int out_size) {
    (void)in_sizes; (void)n_in; (void)out_size;
    static EncodeFn enc = nullptr;
    static void* qabs_ptr = nullptr;
    static bool fits = false;
    if (!enc) {
        void* fn = nullptr;
        cudaDriverEntryPointQueryResult st;
        cudaGetDriverEntryPoint("cuTensorMapEncodeTiled", &fn, cudaEnableDefault, &st);
        enc = (EncodeFn)fn;
        cudaFuncSetAttribute(fused_kernel, cudaFuncAttributeMaxDynamicSharedMemorySize, SMEM_BYTES);
        cudaGetSymbolAddress(&qabs_ptr, g_qabs);
        cudaLaunchConfig_t cfg = {};
        cfg.gridDim = dim3(NCTA);
        cfg.blockDim = dim3(NTHREADS);
        cfg.dynamicSmemBytes = SMEM_BYTES;
        cudaLaunchAttribute at[1];
        at[0].id = cudaLaunchAttributeClusterDimension;
        at[0].val.clusterDim.x = 2; at[0].val.clusterDim.y = 1; at[0].val.clusterDim.z = 1;
        cfg.attrs = at;
        cfg.numAttrs = 1;
        int nclusters = 0;
        if (cudaOccupancyMaxActiveClusters(&nclusters, fused_kernel, &cfg) != cudaSuccess) { (void)cudaGetLastError(); nclusters = NCTA / 2; }
        fits = nclusters >= NCTA / 2;
        if (!fits) fprintf(stderr, "fused_kernel: only %d of %d clusters can be resident on this device\n", nclusters, NCTA / 2);
    }
    if (!enc || !fits) return;
    Params p;
    map2d(enc, &p.kv, d_in[1], 16384, 512, 64, 64, CU_TENSOR_MAP_SWIZZLE_128B);
    map2d(enc, &p.wq, d_in[2], 512, 4096, 64, 64, CU_TENSOR_MAP_SWIZZLE_128B);
    map2d(enc, &p.wuk, d_in[3], 512, 4096, 64, 64, CU_TENSOR_MAP_SWIZZLE_128B);
    map2d(enc, &p.wuv, d_in[4], 512, 4096, 64, 64, CU_TENSOR_MAP_SWIZZLE_128B);
    map3d(enc, &p.wo, d_in[5], 4096, 32, 2);
    map2d(enc, &p.w1, d_in[7], 512, 1376, 256, 16, CU_TENSOR_MAP_SWIZZLE_32B);
    map3d(enc, &p.w2, d_in[8], 1376, 16, 4);
    map2d(enc, &p.wmod, d_in[10], 512, 3072, 256, 16, CU_TENSOR_MAP_SWIZZLE_32B);
    map3d(enc, &p.qabs, qabs_ptr, 128, 32, 4);
    map2d(enc, &p.wmoda, d_in[10], 512, 3072, 128, 16, CU_TENSOR_MAP_SWIZZLE_32B);
    p.x = (const __nv_bfloat16*)d_in[0];
    p.c = (const __nv_bfloat16*)d_in[9];
    p.out = (__nv_bfloat16*)d_out;
    fused_kernel<<<NCTA, NTHREADS, SMEM_BYTES, cudaStreamPerThread>>>(p);
}
```

```cpp
#include <cuda_runtime.h>
#include <cuda_bf16.h>
#include <cuda.h>
#include <stdint.h>
#include <stdio.h>

namespace {

constexpr int NCTA = 128;
constexpr int NTHREADS = 320;
constexpr int NFFN = 86;
#define WINDOW 5
#define DT_0 500
#define DT_F 340
#define DT_S 325
#define DT_T 320
#define DT_T2 300
#define QK_EARLY 4
#define GATE_NS 3600
#define STAT_LEAD 200
#define G6ADELAY 450
#define HOPDELAY 300
#define FFNDELAY 2300

constexpr uint32_t OFF_KV = 0;
constexpr uint32_t OFF_X = 131072;
constexpr uint32_t OFF_Y = 163840;
constexpr uint32_t OFF_Z = 196608;
constexpr uint32_t OFF_P = 212992;
constexpr uint32_t OFF_S = 221184;
constexpr uint32_t OFF_ACT = 225344;
constexpr uint32_t OFF_RED = 227648;
constexpr uint32_t OFF_BAR = 229696;
constexpr uint32_t OFF_MISC = 230208;
constexpr uint32_t SMEM_BYTES = 230720;
constexpr uint32_t OFF_STG = OFF_KV;
constexpr uint32_t OFF_XCH = OFF_KV + 16384;
constexpr uint32_t OFF_W2 = OFF_KV + 32768;
constexpr uint32_t OFF_SBCB = OFF_KV + 49152;
constexpr uint32_t OFF_SCR = OFF_KV + 65536;

enum {
    B_WQ = 0,
    B_WUK = 4,
    B_KV = 8,
    B_MOD = 24,
    B_WUV = 26,
    B_WO = 30,
    B_W1 = 34,
    B_W2 = 36,
    B_QABS = 38,
    B_YFREE = 39,
    B_XFREE = 40,
    B_ZFREE = 41,
    B_KV0FREE = 42,
    B_P3 = 43,
    B_CLR2 = 44,
    B_MODV = 45,
    B_WA = 46,
    B_EP = 47,
    B_PEER0 = 48,
    B_XCH = 49,
    B_G4 = 50,
    B_XST = 51,
    B_COUNT = 52
};

struct alignas(64) Params {
    CUtensorMap kv, wq, wuk, wuv, wo, w1, w2, wmod, qabs, wmoda;
    const __nv_bfloat16* x;
    const __nv_bfloat16* c;
    __nv_bfloat16* out;
};

__device__ __align__(128) uint4 g_H[128 * 32];
__device__ __align__(128) uint4 g_Q[128 * 128];
__device__ __align__(128) __nv_bfloat16 g_qabs[4 * 32 * 512];
__device__ __align__(128) uint4 g_part[128 * 4 * 16 * 16];
__device__ __align__(128) uint4 g_stat[8 * 64 * 2];
__device__ __align__(128) uint4 g_C[128 * 128];
__device__ __align__(128) uint2 g_O[128 * 512];
__device__ __align__(128) uint2 g_X1[128 * 8];
__device__ __align__(128) uint2 g_F[NFFN * 512];
__device__ __align__(128) uint4 g_M[4 * 512];
constexpr int NSYNC = 8;
__device__ __align__(128) unsigned int g_sync[NSYNC * 32];

__device__ __forceinline__ uint32_t smem_u32(const void* p) { return (uint32_t)__cvta_generic_to_shared(p); }
__device__ __forceinline__ void mbar_init(uint32_t bar, int cnt) { asm volatile("mbarrier.init.shared::cta.b64 [%0], %1;" ::"r"(bar), "r"(cnt) : "memory"); }
__device__ __forceinline__ void mbar_expect_tx(uint32_t bar, uint32_t bytes) { asm volatile("mbarrier.arrive.expect_tx.shared::cta.b64 _, [%0], %1;" ::"r"(bar), "r"(bytes) : "memory"); }
__device__ __forceinline__ void mbar_arrive(uint32_t bar) { asm volatile("mbarrier.arrive.shared::cta.b64 _, [%0];" ::"r"(bar) : "memory"); }
constexpr int SPIN_LIMIT = 1 << 20;
__device__ __forceinline__ void mbar_wait(uint32_t bar) {
    asm volatile("{\n.reg .pred p;\n.reg .u32 n;\nmov.u32 n, 0;\n"
                 "LW:\nmbarrier.try_wait.parity.shared::cta.b64 p, [%0], 0;\n@p bra LD;\n"
                 "add.u32 n, n, 1;\nsetp.lt.u32 p, n, 262144;\n@p bra LW;\nLD:\n}" ::"r"(bar) : "memory");
}
__device__ __forceinline__ void mbar_wait_n(uint32_t bar, int n) {
#pragma unroll 1
    for (int k = 0; k < n; k++) mbar_wait(bar + k * 8);
}
__device__ __forceinline__ void bar_main() { asm volatile("bar.sync 1, 256;" ::: "memory"); }
__device__ __forceinline__ void fence_async_smem() { asm volatile("fence.proxy.async.shared::cta;" ::: "memory"); }

__device__ __forceinline__ uint4 ld128(const uint4* p) {
    uint4 v;
    asm volatile("{\n.reg .b128 t;\n.reg .b64 lo, hi;\nld.relaxed.gpu.global.b128 t, [%4];\nmov.b128 {lo, hi}, t;\nmov.b64 {%0,%1}, lo;\nmov.b64 {%2,%3}, hi;\n}"
                 : "=r"(v.x), "=r"(v.y), "=r"(v.z), "=r"(v.w) : "l"(p) : "memory");
    return v;
}
__device__ __forceinline__ void st128(uint4* p, uint4 v) {
    asm volatile("{\n.reg .b128 t;\n.reg .b64 lo, hi;\nmov.b64 lo, {%1,%2};\nmov.b64 hi, {%3,%4};\nmov.b128 t, {lo, hi};\nst.relaxed.gpu.global.b128 [%0], t;\n}"
                 ::"l"(p), "r"(v.x), "r"(v.y), "r"(v.z), "r"(v.w) : "memory");
}
__device__ __forceinline__ uint4 ldnc128_if(const void* p, bool c) {
    uint4 v;
    asm volatile("{\n.reg .pred p;\nsetp.ne.u32 p, %5, 0;\nmov.u32 %0, 0;\nmov.u32 %1, 0;\nmov.u32 %2, 0;\nmov.u32 %3, 0;\n@p ld.global.nc.v4.u32 {%0,%1,%2,%3}, [%4];\n}"
                 : "=r"(v.x), "=r"(v.y), "=r"(v.z), "=r"(v.w) : "l"(p), "r"((uint32_t)c));
    return v;
}
__device__ __forceinline__ uint32_t ldnc32(const void* p) { uint32_t v; asm volatile("ld.global.nc.u32 %0, [%1];" : "=r"(v) : "l"(p)); return v; }
__device__ __forceinline__ uint32_t ldnc16(const void* p) { uint32_t v; asm volatile("ld.global.nc.u16 %0, [%1];" : "=r"(v) : "l"(p)); return v; }
__device__ __forceinline__ unsigned int ld_epoch(const unsigned int* p) { unsigned int v; asm volatile("ld.relaxed.gpu.global.u32 %0, [%1];" : "=r"(v) : "l"(p)); return v; }
__device__ __forceinline__ void put4(uint4* p, float a, float b, float c, float d, uint32_t tag) {
    st128(p, make_uint4((__float_as_uint(a) & ~3u) | tag, __float_as_uint(b), __float_as_uint(c), __float_as_uint(d)));
}
__device__ __forceinline__ float4 as_f4(uint4 v) {
    return make_float4(__uint_as_float(v.x & ~3u), __uint_as_float(v.y), __uint_as_float(v.z), __uint_as_float(v.w));
}
__device__ __forceinline__ void add4(float4& a, const float4& b) { a.x += b.x; a.y += b.y; a.z += b.z; a.w += b.w; }
__device__ __forceinline__ float4 get4(const uint4* p, bool act, uint32_t tag) {
    uint4 v = make_uint4(tag, 0, 0, 0);
    int it = 0;
#pragma unroll 1
    do { if (act) v = ld128(p); } while (!__all_sync(~0u, (v.x & 3u) == tag) && ++it < SPIN_LIMIT);
    return as_f4(v);
}
__device__ __forceinline__ uint2 ld64(const uint2* p) { uint2 v; asm volatile("{\n.reg .b64 t;\nld.relaxed.gpu.global.b64 t, [%2];\nmov.b64 {%0,%1}, t;\n}" : "=r"(v.x), "=r"(v.y) : "l"(p) : "memory"); return v; }
__device__ __forceinline__ void st64(uint2* p, uint32_t x, uint32_t y) { asm volatile("{\n.reg .b64 t;\nmov.b64 t, {%1,%2};\nst.relaxed.gpu.global.b64 [%0], t;\n}" ::"l"(p), "r"(x), "r"(y) : "memory"); }
__device__ __forceinline__ uint32_t pack_bf16(float lo, float hi);
__device__ __forceinline__ void put2(uint2* p, float a, float b, float c, float d, uint32_t par) { st64(p, (pack_bf16(a, b) & ~1u) | par, pack_bf16(c, d)); }
__device__ __forceinline__ float4 as_f4(uint2 v) {
    return make_float4(__uint_as_float(v.x << 16), __uint_as_float(v.x & 0xffff0000u), __uint_as_float(v.y << 16), __uint_as_float(v.y & 0xffff0000u));
}
__device__ __forceinline__ float4 get4sum4(const uint4* p0, int stride, uint32_t tag) {
    uint4 u0, u1, u2, u3;
    int it = 0;
#pragma unroll 1
    do { u0 = ld128(p0); u1 = ld128(p0 + stride); u2 = ld128(p0 + 2 * stride); u3 = ld128(p0 + 3 * stride); }
    while (!__all_sync(~0u, ((u0.x ^ tag) & 3u) == 0 && ((u1.x ^ tag) & 3u) == 0 && ((u2.x ^ tag) & 3u) == 0 && ((u3.x ^ tag) & 3u) == 0) && ++it < SPIN_LIMIT);
    float4 a = as_f4(u0), b = as_f4(u2);
    add4(a, as_f4(u1));
    add4(b, as_f4(u3));
    add4(a, b);
    return a;
}
__device__ __forceinline__ uint32_t pack_bf16(float lo, float hi) {
    uint32_t r;
    asm("cvt.rn.bf16x2.f32 %0, %1, %2;" : "=r"(r) : "f"(hi), "f"(lo));
    return r;
}
__device__ __forceinline__ float bf_lo(uint32_t u) { return __uint_as_float(u << 16); }
__device__ __forceinline__ float bf_hi(uint32_t u) { return __uint_as_float(u & 0xffff0000u); }
__device__ __forceinline__ float ex2(float x) { float y; asm("ex2.approx.ftz.f32 %0, %1;" : "=f"(y) : "f"(x)); return y; }

__device__ __forceinline__ void ldsm4(uint32_t (&r)[4], uint32_t addr) {
    asm volatile("ldmatrix.sync.aligned.m8n8.x4.shared.b16 {%0,%1,%2,%3}, [%4];" : "=r"(r[0]), "=r"(r[1]), "=r"(r[2]), "=r"(r[3]) : "r"(addr) : "memory");
}
__device__ __forceinline__ void ldsm4t(uint32_t (&r)[4], uint32_t addr) {
    asm volatile("ldmatrix.sync.aligned.m8n8.x4.trans.shared.b16 {%0,%1,%2,%3}, [%4];" : "=r"(r[0]), "=r"(r[1]), "=r"(r[2]), "=r"(r[3]) : "r"(addr) : "memory");
}
__device__ __forceinline__ void stsm4t(uint32_t addr, uint32_t r0, uint32_t r1, uint32_t r2, uint32_t r3) {
    asm volatile("stmatrix.sync.aligned.m8n8.x4.trans.shared.b16 [%0], {%1,%2,%3,%4};" ::"r"(addr), "r"(r0), "r"(r1), "r"(r2), "r"(r3) : "memory");
}
__device__ __forceinline__ void mma16816(float (&d)[4], const uint32_t (&a)[4], uint32_t b0, uint32_t b1) {
    asm volatile("mma.sync.aligned.m16n8k16.row.col.f32.bf16.bf16.f32 {%0,%1,%2,%3}, {%4,%5,%6,%7}, {%8,%9}, {%0,%1,%2,%3};"
                 : "+f"(d[0]), "+f"(d[1]), "+f"(d[2]), "+f"(d[3]) : "r"(a[0]), "r"(a[1]), "r"(a[2]), "r"(a[3]), "r"(b0), "r"(b1));
}
__device__ __forceinline__ void sts32(uint32_t a, uint32_t v) { asm volatile("st.shared.b32 [%0], %1;" ::"r"(a), "r"(v) : "memory"); }
__device__ __forceinline__ void sts16(uint32_t a, float v) {
    __nv_bfloat16 h = __float2bfloat16_rn(v);
    asm volatile("st.shared.b16 [%0], %1;" ::"r"(a), "h"(*reinterpret_cast<unsigned short*>(&h)) : "memory");
}
__device__ __forceinline__ void stsf(uint32_t a, float v) { asm volatile("st.shared.f32 [%0], %1;" ::"r"(a), "f"(v) : "memory"); }
__device__ __forceinline__ void stsf4(uint32_t a, float4 v) { asm volatile("st.shared.v4.f32 [%0], {%1,%2,%3,%4};" ::"r"(a), "f"(v.x), "f"(v.y), "f"(v.z), "f"(v.w) : "memory"); }
__device__ __forceinline__ uint32_t lds32(uint32_t a) { uint32_t v; asm volatile("ld.shared.b32 %0, [%1];" : "=r"(v) : "r"(a) : "memory"); return v; }
__device__ __forceinline__ float ldsf(uint32_t a) { float v; asm volatile("ld.shared.f32 %0, [%1];" : "=f"(v) : "r"(a) : "memory"); return v; }
__device__ __forceinline__ float2 ldsf2(uint32_t a) { float2 v; asm volatile("ld.shared.v2.f32 {%0,%1}, [%2];" : "=f"(v.x), "=f"(v.y) : "r"(a) : "memory"); return v; }
__device__ __forceinline__ float4 ldsf4(uint32_t a) { float4 v; asm volatile("ld.shared.v4.f32 {%0,%1,%2,%3}, [%4];" : "=f"(v.x), "=f"(v.y), "=f"(v.z), "=f"(v.w) : "r"(a) : "memory"); return v; }
__device__ __forceinline__ uint4 lds128(uint32_t a) { uint4 v; asm volatile("ld.shared.v4.b32 {%0,%1,%2,%3}, [%4];" : "=r"(v.x), "=r"(v.y), "=r"(v.z), "=r"(v.w) : "r"(a) : "memory"); return v; }

__device__ __forceinline__ void tma2d(uint32_t dst, const CUtensorMap* m, int c0, int c1, uint32_t bar, uint32_t bytes, uint64_t pol) {
    asm volatile("{\n.reg .pred p;\nelect.sync _|p, 0xffffffff;\n"
                 "@p mbarrier.arrive.expect_tx.shared::cta.b64 _, [%2], %6;\n"
                 "@p cp.async.bulk.tensor.2d.shared::cluster.global.mbarrier::complete_tx::bytes.L2::cache_hint [%0], [%1, {%3, %4}], [%2], %5;\n}"
                 ::"r"(dst), "l"(m), "r"(bar), "r"(c0), "r"(c1), "l"(pol), "r"(bytes) : "memory");
}
__device__ __forceinline__ void tma3d(uint32_t dst, const CUtensorMap* m, int c0, int c1, int c2, uint32_t bar, uint32_t bytes, uint64_t pol) {
    asm volatile("{\n.reg .pred p;\nelect.sync _|p, 0xffffffff;\n"
                 "@p mbarrier.arrive.expect_tx.shared::cta.b64 _, [%2], %7;\n"
                 "@p cp.async.bulk.tensor.3d.shared::cluster.global.mbarrier::complete_tx::bytes.L2::cache_hint [%0], [%1, {%3, %4, %5}], [%2], %6;\n}"
                 ::"r"(dst), "l"(m), "r"(bar), "r"(c0), "r"(c1), "r"(c2), "l"(pol), "r"(bytes) : "memory");
}
__device__ __forceinline__ void tma2d_na(uint32_t dst, const CUtensorMap* m, int c0, int c1, uint32_t bar, uint64_t pol) {
    asm volatile("{\n.reg .pred p;\nelect.sync _|p, 0xffffffff;\n"
                 "@p cp.async.bulk.tensor.2d.shared::cluster.global.mbarrier::complete_tx::bytes.L2::cache_hint [%0], [%1, {%3, %4}], [%2], %5;\n}"
                 ::"r"(dst), "l"(m), "r"(bar), "r"(c0), "r"(c1), "l"(pol) : "memory");
}
__device__ __forceinline__ uint32_t mapa(uint32_t addr, uint32_t rank) {
    uint32_t r;
    asm("mapa.shared::cluster.u32 %0, %1, %2;" : "=r"(r) : "r"(addr), "r"(rank));
    return r;
}
__device__ __forceinline__ void st_async4(uint32_t raddr, uint32_t a, uint32_t b, uint32_t c, uint32_t d, uint32_t rbar) {
    asm volatile("st.async.weak.shared::cluster.mbarrier::complete_tx::bytes.v4.b32 [%0], {%1,%2,%3,%4}, [%5];" ::"r"(raddr), "r"(a), "r"(b), "r"(c), "r"(d), "r"(rbar) : "memory");
}
__device__ __forceinline__ void st_async2(uint32_t raddr, float a, float b, uint32_t rbar) {
    asm volatile("st.async.weak.shared::cluster.mbarrier::complete_tx::bytes.v2.f32 [%0], {%1,%2}, [%3];" ::"r"(raddr), "f"(a), "f"(b), "r"(rbar) : "memory");
}
__device__ __forceinline__ void tma3d_mc(uint32_t dst, const CUtensorMap* m, int c0, int c1, int c2, uint32_t bar, uint32_t bytes) {
    asm volatile("{\n.reg .pred p;\nelect.sync _|p, 0xffffffff;\n"
                 "@p mbarrier.arrive.expect_tx.shared::cta.b64 _, [%2], %6;\n"
                 "@p cp.async.bulk.tensor.3d.shared::cluster.global.mbarrier::complete_tx::bytes.multicast::cluster [%0], [%1, {%3, %4, %5}], [%2], %7;\n}"
                 ::"r"(dst), "l"(m), "r"(bar), "r"(c0), "r"(c1), "r"(c2), "r"(bytes), "h"((unsigned short)3) : "memory");
}
__device__ __forceinline__ void bulk_s2g(void* dst, uint32_t src, uint32_t bytes) {
    asm volatile("cp.async.bulk.global.shared::cta.bulk_group [%0], [%1], %2;" ::"l"(dst), "r"(src), "r"(bytes) : "memory");
}
__device__ __forceinline__ void prefetch_map(const CUtensorMap* m) { asm volatile("prefetch.tensormap [%0];" ::"l"(m) : "memory"); }

constexpr uint32_t DESC_HI = 64u | (1u << 30);
__device__ __forceinline__ constexpr uint32_t desc_lo(uint32_t addr) { return ((addr & 0x3FFFF) >> 4) | (1u << 16); }
__device__ __forceinline__ void wg_fence() { asm volatile("wgmma.fence.sync.aligned;" ::: "memory"); }
__device__ __forceinline__ void wg_commit() { asm volatile("wgmma.commit_group.sync.aligned;" ::: "memory"); }
__device__ __forceinline__ void wg_wait0() { asm volatile("wgmma.wait_group.sync.aligned 0;" ::: "memory"); }
template <int TA>
__device__ __forceinline__ void wgmma_n32(float (&d)[16], uint32_t alo, uint32_t blo, int scale_d) {
    asm volatile("{\n.reg .pred p;\n.reg .b64 da, db;\nsetp.ne.b32 p, %18, 0;\nmov.b64 da, {%16, %20};\nmov.b64 db, {%17, %20};\n"
                 "wgmma.mma_async.sync.aligned.m64n32k16.f32.bf16.bf16 "
                 "{%0,%1,%2,%3,%4,%5,%6,%7,%8,%9,%10,%11,%12,%13,%14,%15}, da, db, p, 1, 1, %19, 0;\n}"
                 : "+f"(d[0]), "+f"(d[1]), "+f"(d[2]), "+f"(d[3]), "+f"(d[4]), "+f"(d[5]), "+f"(d[6]), "+f"(d[7]),
                   "+f"(d[8]), "+f"(d[9]), "+f"(d[10]), "+f"(d[11]), "+f"(d[12]), "+f"(d[13]), "+f"(d[14]), "+f"(d[15])
                 : "r"(alo), "r"(blo), "r"(scale_d), "n"(TA), "n"(DESC_HI));
}
template <int N>
__device__ __forceinline__ void reg_fence(float (&d)[N]) {
#pragma unroll
    for (int i = 0; i < N; i++) asm volatile("" : "+f"(d[i])::"memory");
}

#define TS(slot)
#define TS0(slot)

__device__ __forceinline__ unsigned int gtimer_lo() {
    unsigned long long t;
    asm volatile("mov.u64 %0, %globaltimer;" : "=l"(t));
    return (unsigned int)t;
}
__device__ __forceinline__ unsigned int clock32() { unsigned int c; asm volatile("mov.u32 %0, %clock;" : "=r"(c)); return c; }
__device__ __forceinline__ void spin(int cycles) {
    if (cycles <= 0) return;
    const unsigned int t0 = clock32();
#pragma unroll 1
    while (clock32() - t0 < (unsigned int)cycles) {}
}
__device__ __forceinline__ unsigned int ld_cnt(const unsigned int* p) {
    unsigned int v;
    asm volatile("ld.relaxed.gpu.global.u32 %0, [%1];" : "=r"(v) : "l"(p) : "memory");
    return v;
}
__device__ __forceinline__ void wait_cnt(const unsigned int* p, unsigned int target) {
    int it = 0;
#pragma unroll 1
    while ((int)(ld_cnt(p) - target) < 0) { if (++it > SPIN_LIMIT) break; }
}
__device__ __forceinline__ void red_cnt(unsigned int* p) { asm volatile("red.relaxed.gpu.global.add.u32 [%0], 1;" ::"l"(p) : "memory"); }

constexpr uint32_t SB0 = 1024;
__device__ __forceinline__ uint32_t smem_base() {
    extern __shared__ __align__(1024) uint8_t smem_dyn[];
    return smem_u32(smem_dyn);
}

__device__ __forceinline__ void gemv_y_load(uint32_t (&a)[8][4]) {
    const int lane = threadIdx.x & 31, warp = threadIdx.x >> 5;
    const int blk = lane >> 3, r8 = lane & 7;
    const int ch = (warp & 3) * 2 + (blk & 1);
    const uint32_t arow = smem_base() + OFF_Y + (warp >> 2) * 16384 + ((blk >> 1) * 8 + r8) * 128 + ((ch ^ r8) << 4);
#pragma unroll
    for (int k = 0; k < 8; k++) ldsm4t(a[k], arow + k * 16 * 128);
}
__device__ __forceinline__ void gemv_y_put(const uint32_t (&a)[8][4], uint4* dst, uint32_t act, uint32_t tag) {
    const int lane = threadIdx.x & 31, warp = threadIdx.x >> 5;
    const uint32_t brow = act + (lane & 3) * 272 + (lane >> 3) * 16;
    uint32_t b[4][4];
#pragma unroll
    for (int k = 0; k < 4; k++) ldsm4(b[k], brow + k * 64);
    float d[4] = {0.f, 0.f, 0.f, 0.f}, e[4] = {0.f, 0.f, 0.f, 0.f};
#pragma unroll
    for (int k = 0; k < 4; k++) {
        mma16816(d, a[2 * k], b[k][0], b[k][1]);
        mma16816(e, a[2 * k + 1], b[k][2], b[k][3]);
    }
    const uint32_t x = (__float_as_uint(d[0] + e[0]) & ~3u) | tag;
    const float y = d[1] + e[1], z = d[2] + e[2], w = d[3] + e[3];
    if ((lane & 3) < 2) st128(dst + warp * 16 + (lane >> 2) * 2 + (lane & 3), make_uint4(x, __float_as_uint(y), __float_as_uint(z), __float_as_uint(w)));
}

__device__ __forceinline__ void gemv_512x16(float (&d)[4], uint32_t tile, uint32_t act, int k0, int nk2, int lane) {
    const int blk = lane >> 3, r8 = lane & 7;
    uint32_t arow = tile + (k0 + (blk >> 1) * 8 + r8) * 32 + (((blk & 1) ^ ((r8 >> 2) & 1)) << 4);
    uint32_t brow = act + (r8 & 3) * 1040 + (k0 + blk * 8) * 2;
#pragma unroll 2
    for (int k2 = 0; k2 < nk2; k2++) {
        uint32_t b[4], a0[4], a1[4];
        ldsm4(b, brow);
        ldsm4t(a0, arow);
        ldsm4t(a1, arow + 512);
        mma16816(d, a0, b[0], b[1]);
        mma16816(d, a1, b[2], b[3]);
        brow += 64;
        arow += 1024;
    }
}

__device__ __noinline__ float4 reduce16(const uint2* base, int n, uint32_t par, int delay) {
    const int t = threadIdx.x, lane = t & 31, warp = t >> 5;
    const uint32_t SCR = smem_base() + OFF_SCR;
    const int pp = t >> 2;
    const uint2* p0 = base + (size_t)pp * 512 + blockIdx.x * 4 + (t & 3);
    const bool act1 = pp + 64 < n;
    spin(delay);
    uint2 u, v = make_uint2(par, 0);
    int it = 0;
#pragma unroll 1
    do { u = ld64(p0); if (act1) v = ld64(p0 + 64 * 512); } while (!__all_sync(~0u, (((u.x ^ par) | (v.x ^ par)) & 1u) == 0) && ++it < SPIN_LIMIT);
    float4 a = as_f4(u);
    if (act1) add4(a, as_f4(v));
#pragma unroll
    for (int of = 4; of <= 16; of <<= 1) {
        a.x += __shfl_xor_sync(~0u, a.x, of); a.y += __shfl_xor_sync(~0u, a.y, of);
        a.z += __shfl_xor_sync(~0u, a.z, of); a.w += __shfl_xor_sync(~0u, a.w, of);
    }
    if (lane < 4) stsf4(SCR + (warp * 4 + lane) * 16, a);
    bar_main();
    float4 r = make_float4(0.f, 0.f, 0.f, 0.f);
    if (t < 4) {
#pragma unroll
        for (int w = 0; w < 8; w++) add4(r, ldsf4(SCR + (w * 4 + t) * 16));
    }
    return r;
}
__device__ __forceinline__ void sts_frag(uint32_t base, uint32_t stride, int m, int b0, float x, float y, float z, float w) {
    const uint32_t a = base + b0 * stride + m * 2;
    sts16(a, x); sts16(a + stride, y); sts16(a + 16, z); sts16(a + stride + 16, w);
}

__global__ void __cluster_dims__(2, 1, 1) __launch_bounds__(NTHREADS, 1) fused_kernel(const __grid_constant__ Params p) {
    extern __shared__ __align__(1024) uint8_t smem[];
    const uint32_t sb = smem_base();
    const int t = threadIdx.x, lane = t & 31;
    const int warp = __shfl_sync(0xffffffffu, t >> 5, 0);
    const int i = blockIdx.x;
    const int hh = i >> 2, jj = i & 3;
    const int bb = i >> 5, chunk = i & 31;
    const uint32_t rank = i & 1;
    auto BAR = [&](int k) { return sb + OFF_BAR + k * 8; };
    const uint32_t MISC = sb + OFF_MISC;

    if (warp == 8) {
        if (lane == 0) {
            TS(0);
            prefetch_map(&p.wmoda);
            prefetch_map(&p.wq);
            mbar_init(BAR(B_WA), 1);
            mbar_init(BAR(0), 1);
            asm volatile("fence.mbarrier_init.release.cluster;" ::: "memory");
            fence_async_smem();
            mbar_expect_tx(BAR(B_WA), 8192);
        }
        __syncwarp();
        uint64_t pol;
        asm volatile("createpolicy.fractional.L2::evict_first.b64 %0, 1.0;" : "=l"(pol));
        tma2d_na(sb + OFF_Z, &p.wmoda, 16 * hh, jj * 128, BAR(B_WA), pol);
        tma2d_na(sb + OFF_Z + 4096, &p.wmoda, 512 + 16 * hh, jj * 128, BAR(B_WA), pol);
        tma2d(sb + OFF_Y, &p.wq, hh * 128, jj * 128, BAR(0), 8192, pol);
        unsigned int due = gtimer_lo() + DT_0;
        if (lane == 0) {
            if ((sb & 0xFFFFFFu) != SB0) __trap();
#pragma unroll
            for (int k = 1; k < 4; k++) mbar_init(BAR(k), 1);
            asm volatile("fence.mbarrier_init.release.cluster;" ::: "memory");
            fence_async_smem();
        }
        __syncwarp();
        asm volatile("bar.arrive 4, 320;" ::: "memory");
        auto pace_dt = [&](int it, unsigned int dt) {
            if (it >= WINDOW) mbar_wait(BAR(0) + (it - WINDOW) * 8);
            int spin_it = 0;
#pragma unroll 1
            while ((int)(gtimer_lo() - due) < 0 && ++spin_it < SPIN_LIMIT) {}
            due += dt;
        };
        auto pace = [&](int it) { pace_dt(it, it < B_KV ? DT_F : (it < B_W1 ? DT_T : DT_T2)); };
        auto tile128 = [&](const CUtensorMap* m, int first, uint32_t dst, int k0) {
#pragma unroll 1
            for (int k = k0; k < 4; k++) {
                pace(first + k);
                tma2d(dst + k * 8192, m, hh * 128 + (k >> 1) * 64, jj * 128 + (k & 1) * 64, BAR(0) + (first + k) * 8, 8192, pol);
            }
        };
        tile128(&p.wq, B_WQ, sb + OFF_Y, 1);
        asm volatile("bar.sync 5, 320;" ::: "memory");
        tile128(&p.wuk, B_WUK, sb + OFF_X, 0);
        TS(61);
#pragma unroll 1
        for (int s = 0; s < 16; s++) {
            pace_dt(B_KV + s, s < 8 ? DT_F : DT_S);
            tma2d(sb + OFF_KV + s * 8192, &p.kv, (s & 7) * 64, bb * 4096 + chunk * 128 + (s >> 3) * 64, BAR(B_KV) + s * 8, 8192, pol);
        }
        const unsigned int t_poll = due + GATE_NS;
        if (lane == 0) sts32(MISC + 232, t_poll);
        TS(43);
        mbar_wait(BAR(B_YFREE));
#pragma unroll 1
        for (int k = 0; k < 2; k++) {
            pace(B_MOD + k);
            tma2d(sb + OFF_Z + k * 8192, &p.wmod, 1024 + 16 * i, k * 256, BAR(B_MOD) + k * 8, 8192, pol);
        }
        tile128(&p.wuv, B_WUV, sb + OFF_Y, 0);
        mbar_wait(BAR(B_XFREE));
#pragma unroll 1
        for (int k = 0; k < 4; k++) {
            pace(B_WO + k);
            tma3d(sb + OFF_X + k * 8192, &p.wo, 0, hh * 128 + jj * 32, k * 2, BAR(B_WO) + k * 8, 8192, pol);
        }
        {
            mbar_wait(BAR(B_EP));
            const unsigned int target = (lds32(MISC + 224) + 1u) * 32u;
            int it = 0;
#pragma unroll 1
            while ((int)(gtimer_lo() - t_poll) < 0 && ++it < SPIN_LIMIT) {}
            it = 0;
#pragma unroll 1
            while (!__all_sync(~0u, (int)(ld_cnt(&g_sync[(lane & 3) * 32 + 1]) - target) >= 0) && ++it < SPIN_LIMIT) {}
            if (lane == 0) mbar_arrive(BAR(B_G4));
            TS(13);
        }
        if (i < NFFN) {
            due = gtimer_lo();
            mbar_wait(BAR(B_ZFREE));
#pragma unroll 1
            for (int k = 0; k < 2; k++) {
                pace(B_W1 + k);
                tma2d(sb + OFF_Z + k * 8192, &p.w1, 16 * i, k * 256, BAR(B_W1) + k * 8, 8192, pol);
            }
            mbar_wait(BAR(B_KV0FREE));
#pragma unroll 1
            for (int k = 0; k < 2; k++) {
                pace(B_W2 + k);
                tma3d(sb + OFF_W2 + k * 8192, &p.w2, 0, 16 * i, k * 4, BAR(B_W2) + k * 8, 8192, pol);
            }
        }
        TS(40);
    } else if (warp == 9) {
        unsigned int ep = 0;
        if (lane == 0) {
            ep = ld_epoch(&g_sync[(i % NSYNC) * 32]);
            mbar_init(BAR(B_YFREE), 8);
            mbar_init(BAR(B_XFREE), 4);
            mbar_init(BAR(B_KV0FREE), 8);
            mbar_init(BAR(B_EP), 1);
            mbar_init(BAR(B_PEER0), 8);
            mbar_init(BAR(B_XCH), 1);
            mbar_init(BAR(B_G4), 1);
            mbar_init(BAR(B_XST), 2);
            mbar_expect_tx(BAR(B_XCH), 16384);
            mbar_expect_tx(BAR(B_XST), 128);
            asm volatile("fence.mbarrier_init.release.cluster;" ::: "memory");
        }
        __syncwarp();
        asm volatile("bar.arrive 5, 320;" ::: "memory");
        asm volatile("bar.arrive 4, 320;" ::: "memory");
        if (lane < 9) prefetch_map(&p.kv + lane);
        const uint4 z = make_uint4(0, 0, 0, 0);
        st128(&g_H[i * 32 + lane], z);
#pragma unroll
        for (int k = 0; k < 4; k++) st128(&g_Q[i * 128 + k * 32 + lane], z);
        uint32_t xr = 0;
        if (lane < 16) {
            const int V = i * 4 + (lane >> 2), e = lane & 3;
            const int m = (V >> 4) * 16 + ((V & 15) >> 1) + (e >> 1) * 8, b = (V & 1) * 2 + (e & 1);
            xr = ldnc16(p.x + b * 512 + m);
        }
        asm volatile("bar.sync 6, 288;" ::: "memory");
        __syncwarp();
        if (lane == 0) {
            sts32(MISC + 224, ep);
            sts32(MISC + 236, 0);
            mbar_arrive(BAR(B_EP));
        }
        mbar_wait(BAR(B_EP));
        ep = lds32(MISC + 224);
        const uint32_t tag = 1u + 2u * (ep & 1u);
        if (lane < 16) stsf(MISC + 32 + lane * 4, __uint_as_float(xr << 16));
        mbar_wait(BAR(B_P3));
        wait_cnt(&g_sync[(4 + (i & 3)) * 32 + 1], (ep + 1u) * 128u);
        __syncwarp();
        tma3d_mc(sb + OFF_X + rank * 16384, &p.qabs, 0, bb * 32, rank * 4, BAR(B_QABS), 32768);
        TS(41);
#pragma unroll 1
        for (int k = 0; k < 4; k++) st128(&g_C[i * 128 + k * 32 + lane], z);
        if (lane < 16) st128(&g_M[i * 16 + lane], z);
        {
            const uint32_t inv = ep & 1u;
            const uint4 zi = make_uint4(inv, 0, inv, 0);
            if (lane < 4) st128(reinterpret_cast<uint4*>(&g_X1[i * 8]) + lane, zi);
#pragma unroll 1
            for (int k = 0; k < 8; k++) {
                st128(reinterpret_cast<uint4*>(&g_O[i * 512]) + k * 32 + lane, zi);
                if (i < NFFN) st128(reinterpret_cast<uint4*>(&g_F[i * 512]) + k * 32 + lane, zi);
                spin(100);
            }
        }
        __syncwarp();
        if (lane == 0) mbar_arrive(BAR(B_CLR2));
        TS(44);
        mbar_wait_n(BAR(B_MOD), 2);
        float d[4] = {0.f, 0.f, 0.f, 0.f};
        gemv_512x16(d, sb + OFF_Z, sb + OFF_S, 0, 16, lane);
        __syncwarp();
        if (lane == 0) mbar_arrive(BAR(B_ZFREE));
        if ((lane & 3) < 2) put4(&g_M[i * 16 + (lane >> 2) * 2 + (lane & 3)], d[0], d[1], d[2], d[3], tag);
        __syncwarp();
        if (lane == 0 && i >= 32 && i < 96) red_cnt(&g_sync[4 * 32 + 2]);
        TS(42);
        {
            const float4 v = get4(&g_M[((lane >> 2) & 1) * 3 * 512 + i * 4 + (lane & 3)], lane < 8, tag);
            if (lane < 8) stsf4(MISC + 96 + lane * 16, v);
        }
        __syncwarp();
        if (lane == 0) {
            if (i < NFFN) {
                wait_cnt(&g_sync[4 * 32 + 2], (ep + 1u) * 64u);
                mbar_wait(BAR(B_KV0FREE));
                asm volatile("fence.proxy.async.global;" ::: "memory");
                mbar_expect_tx(BAR(B_MODV), 16384);
                asm volatile("cp.async.bulk.shared::cluster.global.mbarrier::complete_tx::bytes [%0], [%1], %2, [%3];"
                             ::"r"(sb + OFF_SBCB), "l"(&g_M[512]), "r"(16384), "r"(BAR(B_MODV)) : "memory");
            } else {
                mbar_arrive(BAR(B_MODV));
            }
            TS(45);
        }
    } else {
        const uint32_t ACT = sb + OFF_ACT, ACTB = sb + OFF_ACT + 1152, RED = sb + OFF_RED;
        const int g = lane >> 2, q = lane & 3;
        const int vrr = (lane & 15) >> 1, vb0 = (lane & 1) * 2;
        uint32_t cw[4];
        uint4 xv[2];
        uint32_t xh[4];
        {
            const uint4* xp = reinterpret_cast<const uint4*>(p.x + (warp & 3) * 512 + lane * 16);
            xv[0] = ldnc128_if(xp, warp < 4);
            xv[1] = ldnc128_if(xp + 1, warp < 4);
            const __nv_bfloat16* xq = p.x + vb0 * 512 + jj * 128 + warp * 16 + vrr;
            xh[0] = ldnc16(xq); xh[1] = ldnc16(xq + 512); xh[2] = ldnc16(xq + 8); xh[3] = ldnc16(xq + 520);
        }
#pragma unroll
        for (int b = 0; b < 4; b++) cw[b] = ldnc32(p.c + b * 512 + 2 * t);
        if (lane == 0) {
#pragma unroll
            for (int k = 0; k < 5; k++) {
                int idx = 4 + warp * 5 + k;
                if (idx >= B_YFREE) idx = (idx == 39) ? B_ZFREE : (idx == 40 ? B_P3 : (idx == 41 ? B_CLR2 : B_MODV));
                mbar_init(BAR(0) + idx * 8, 1);
            }
            asm volatile("fence.mbarrier_init.release.cluster;" ::: "memory");
        }
        __syncwarp();
        asm volatile("bar.arrive 5, 320;" ::: "memory");
        asm volatile("bar.arrive 6, 288;" ::: "memory");
        asm volatile("bar.sync 4, 320;" ::: "memory");

#pragma unroll
        for (int b = 0; b < 4; b++) {
            const float c0 = bf_lo(cw[b]), c1 = bf_hi(cw[b]);
            sts32(sb + OFF_S + b * 1040 + t * 4, pack_bf16(__fdividef(c0, 1.f + __expf(-c0)), __fdividef(c1, 1.f + __expf(-c1))));
        }
        if (warp < 4) {
            const uint32_t u[8] = {xv[0].x, xv[0].y, xv[0].z, xv[0].w, xv[1].x, xv[1].y, xv[1].z, xv[1].w};
            float s = 0.f, ss = 0.f;
#pragma unroll
            for (int k = 0; k < 8; k++) s += bf_lo(u[k]) + bf_hi(u[k]);
#pragma unroll
            for (int o = 16; o; o >>= 1) s += __shfl_xor_sync(~0u, s, o);
            const float mean = s * (1.f / 512.f);
#pragma unroll
            for (int k = 0; k < 8; k++) { const float d0 = bf_lo(u[k]) - mean, d1 = bf_hi(u[k]) - mean; ss += d0 * d0 + d1 * d1; }
#pragma unroll
            for (int o = 16; o; o >>= 1) ss += __shfl_xor_sync(~0u, ss, o);
            if (lane == 0) { stsf(MISC + warp * 8, mean); stsf(MISC + warp * 8 + 4, rsqrtf(ss * (1.f / 512.f) + 1e-5f)); }
        }
        bar_main();
        mbar_wait(BAR(B_EP));
        const unsigned int ep = lds32(MISC + 224);
        const uint32_t tag = 1u + 2u * (ep & 1u);
        const uint32_t par = (ep & 1u) ^ 1u;
        if (warp < 2) {
            mbar_wait(BAR(B_WA));
            TS0(26);
            float d[4] = {0.f, 0.f, 0.f, 0.f};
            gemv_512x16(d, sb + OFF_Z + warp * 4096 - jj * 4096, sb + OFF_S, jj * 128, 4, lane);
            if (q < 2) put4(&g_H[i * 32 + warp * 16 + g * 2 + q], d[0], d[1], d[2], d[3], tag);
        }
        TS0(1);
        mbar_wait_n(BAR(B_WQ), 4);
        uint32_t afr[8][4];
        gemv_y_load(afr);
        TS0(3);
        {
            const float4 a = get4sum4(&g_H[(4 * (8 * jj + warp)) * 32 + lane], 32, tag);
            const float cx = __shfl_down_sync(~0u, a.x, 16), cy = __shfl_down_sync(~0u, a.y, 16);
            const float cz = __shfl_down_sync(~0u, a.z, 16), cwv = __shfl_down_sync(~0u, a.w, 16);
            if (lane < 16) {
                const float2 s0 = ldsf2(MISC + vb0 * 8), s1 = ldsf2(MISC + vb0 * 8 + 8);
                sts_frag(ACT, 272, warp * 16 + vrr, vb0,
                         (__uint_as_float(xh[0] << 16) - s0.x) * s0.y * (1.f + cx) + a.x,
                         (__uint_as_float(xh[1] << 16) - s1.x) * s1.y * (1.f + cy) + a.y,
                         (__uint_as_float(xh[2] << 16) - s0.x) * s0.y * (1.f + cz) + a.z,
                         (__uint_as_float(xh[3] << 16) - s1.x) * s1.y * (1.f + cwv) + a.w);
            }
        }
        bar_main();
        TS0(2);
        gemv_y_put(afr, &g_Q[i * 128], ACT, tag);
        __syncwarp();
        if (lane == 0) mbar_arrive(BAR(B_YFREE));
        mbar_wait_n(BAR(B_WUK), 4);
        TS0(5);
        if (warp < 4) {
            const float4 a = get4sum4(&g_Q[hh * 4 * 128 + t], 128, tag);
            sts_frag(ACTB, 272, (t >> 4) * 16 + vrr, vb0, a.x, a.y, a.z, a.w);
        }
        bar_main();
        TS0(4);
        {
            float d[4] = {0.f, 0.f, 0.f, 0.f};
            const int blk = lane >> 3, r8 = lane & 7;
            const uint32_t arow = sb + OFF_X + (warp * 16 + (blk & 1) * 8 + r8) * 128;
            const uint32_t brow = ACTB + (r8 & 3) * 272 + blk * 16;
            uint32_t a[8][4], b[4][4];
#pragma unroll
            for (int k = 0; k < 8; k++) ldsm4(a[k], arow + (k >> 2) * 16384 + ((((k & 3) * 2 + (blk >> 1)) ^ r8) << 4));
#pragma unroll
            for (int k = 0; k < 4; k++) ldsm4(b[k], brow + k * 64);
            float e[4] = {0.f, 0.f, 0.f, 0.f};
#pragma unroll
            for (int k = 0; k < 4; k++) {
                mma16816(d, a[2 * k], b[k][0], b[k][1]);
                mma16816(e, a[2 * k + 1], b[k][2], b[k][3]);
            }
            d[0] += e[0]; d[1] += e[1]; d[2] += e[2]; d[3] += e[3];
            const float sc = 0.08838834764831845f * 1.4426950408889634f;
            if (q < 2) sts_frag(RED, 256, warp * 16 + g, 2 * q, d[0] * sc, d[1] * sc, d[2] * sc, d[3] * sc);
            fence_async_smem();
            bar_main();
            if (t == 0) {
#pragma unroll 1
                for (int b = 0; b < 4; b++) bulk_s2g(&g_qabs[(b * 32 + hh) * 512 + jj * 128], RED + b * 256, 256);
                asm volatile("cp.async.bulk.commit_group;" ::: "memory");
                asm volatile("cp.async.bulk.wait_group 0;" ::: "memory");
#pragma unroll
                for (int r = 0; r < 4; r++) red_cnt(&g_sync[(4 + r) * 32 + 1]);
                mbar_arrive(BAR(B_P3));
            }
            TS0(6);
        }
        const int wg = warp >> 2, wq = warp & 3;
        {
            const uint32_t MX = RED;
            const uint32_t LRED = RED + 512;
            const uint32_t OST = ACTB + 128, PST = ACTB;
            const uint32_t ALPHA = RED + 1536, MRUN = RED + 1664;
            float o[4][16];
            float lsum[8];
#pragma unroll
            for (int k = 0; k < 8; k++) lsum[k] = 0.f;
            if (t < 32) stsf(MRUN + t * 4, -INFINITY);
            mbar_wait(BAR(B_QABS));
            TS0(7);
            float s[16];
            auto qk = [&](int c0, int c1) {
                uint32_t da = desc_lo(SB0 + OFF_KV) + wg * (65536 >> 4) + c0 * (8192 >> 4), db = desc_lo(SB0 + OFF_X) + c0 * (4096 >> 4);
#pragma unroll 1
                for (int cb = c0; cb < c1; cb++) {
                    mbar_wait(BAR(B_KV) + (wg * 8 + cb) * 8);
                    wg_fence();
#pragma unroll
                    for (int k = 0; k < 4; k++) wgmma_n32<0>(s, da + k * 2, db + k * 2, (cb | k) != 0);
                    wg_commit();
                    da += 8192 >> 4;
                    db += 4096 >> 4;
                }
            };
            if (wg == 1) qk(0, QK_EARLY);
#pragma unroll 1
            for (int tile = 0; tile < 2; tile++) {
                if (wg == tile) {
                    qk(tile == 0 ? 0 : QK_EARLY, 8);
                    wg_wait0();
                    reg_fence(s);
                    if (tile == 1) {
                        __syncwarp();
                        if (lane == 0) {
                            mbar_arrive(BAR(B_XFREE));
                            mbar_arrive(BAR(B_KV0FREE));
                            asm volatile("mbarrier.arrive.relaxed.cluster.shared::cluster.b64 _, [%0];" ::"r"(mapa(BAR(B_PEER0), rank ^ 1)) : "memory");
                        }
                    }
                    if (wq == 0) TS(8 + tile * 2);
                    float m[8];
#pragma unroll
                    for (int jb = 0; jb < 4; jb++) {
                        m[2 * jb] = fmaxf(s[4 * jb], s[4 * jb + 2]);
                        m[2 * jb + 1] = fmaxf(s[4 * jb + 1], s[4 * jb + 3]);
                    }
                    {
                        const bool u4 = lane & 16, u3 = lane & 8, u2 = lane & 4;
                        float h4[4], h2[2];
#pragma unroll
                        for (int k = 0; k < 4; k++) h4[k] = fmaxf(u4 ? m[k + 4] : m[k], __shfl_xor_sync(~0u, u4 ? m[k] : m[k + 4], 16));
#pragma unroll
                        for (int k = 0; k < 2; k++) h2[k] = fmaxf(u3 ? h4[k + 2] : h4[k], __shfl_xor_sync(~0u, u3 ? h4[k] : h4[k + 2], 8));
                        const float h1 = fmaxf(u2 ? h2[1] : h2[0], __shfl_xor_sync(~0u, u2 ? h2[0] : h2[1], 4));
                        stsf(MX + (wq * 32 + 8 * (g >> 1) + 2 * q + (g & 1)) * 4, h1);
                    }
                    if (tile == 0) asm volatile("bar.sync 2, 128;" ::: "memory"); else asm volatile("bar.sync 3, 128;" ::: "memory");
                    const float mold = ldsf(MRUN + tile * 128 + lane * 4);
                    const float mnew = fmaxf(fmaxf(fmaxf(ldsf(MX + lane * 4), ldsf(MX + 128 + lane * 4)), fmaxf(ldsf(MX + 256 + lane * 4), ldsf(MX + 384 + lane * 4))), mold);
                    uint32_t lo[4], hi[4];
#pragma unroll
                    for (int jb = 0; jb < 4; jb++) {
                        const float m0 = __shfl_sync(~0u, mnew, 8 * jb + 2 * q), m1 = __shfl_sync(~0u, mnew, 8 * jb + 2 * q + 1);
                        lo[jb] = pack_bf16(ex2(s[4 * jb] - m0), ex2(s[4 * jb + 1] - m1));
                        hi[jb] = pack_bf16(ex2(s[4 * jb + 2] - m0), ex2(s[4 * jb + 3] - m1));
                        lsum[2 * jb] = bf_lo(lo[jb]) + bf_lo(hi[jb]);
                        lsum[2 * jb + 1] = bf_hi(lo[jb]) + bf_hi(hi[jb]);
                    }
                    const uint32_t prow = sb + OFF_P + tile * 4096 + ((lane + 16 * rank) & 31) * 128;
                    stsm4t(prow + (((2 * wq) ^ (lane & 7)) << 4), lo[0], lo[1], lo[2], lo[3]);
                    stsm4t(prow + (((2 * wq + 1) ^ (lane & 7)) << 4), hi[0], hi[1], hi[2], hi[3]);
                    fence_async_smem();
                    if (wq == 0) { stsf(ALPHA + lane * 4, ex2(mold - mnew)); stsf(MRUN + (tile + 1) * 128 + lane * 4, mnew); }
                }
                bar_main();
                TS0(27 + tile);
                if (tile == 1) {
                    wg_wait0();
#pragma unroll
                    for (int mt = 0; mt < 4; mt++) reg_fence(o[mt]);
#pragma unroll
                    for (int jb = 0; jb < 4; jb++) {
                        const float2 a = ldsf2(ALPHA + ((8 * jb + 2 * q + 16 * rank) & 31) * 4);
#pragma unroll
                        for (int mt = 0; mt < 4; mt++) { o[mt][4 * jb] *= a.x; o[mt][4 * jb + 1] *= a.y; o[mt][4 * jb + 2] *= a.x; o[mt][4 * jb + 3] *= a.y; }
                    }
                }
                {
                    const uint32_t da = desc_lo(SB0 + OFF_KV) + tile * (65536 >> 4) + wg * (32768 >> 4), db = desc_lo(SB0 + OFF_P) + tile * (4096 >> 4);
                    wg_fence();
#pragma unroll
                    for (int mt = 0; mt < 4; mt++) {
#pragma unroll
                        for (int k = 0; k < 4; k++)
                            wgmma_n32<1>(o[mt], da + mt * (8192 >> 4) + k * (2048 >> 4), db + k * 2, tile | k);
                        wg_commit();
                    }
                }
                if (wg == tile) {
                    {
                        const bool u4 = lane & 16, u3 = lane & 8, u2 = lane & 4;
                        float h4[4], h2[2];
#pragma unroll
                        for (int k = 0; k < 4; k++) h4[k] = (u4 ? lsum[k + 4] : lsum[k]) + __shfl_xor_sync(~0u, u4 ? lsum[k] : lsum[k + 4], 16);
#pragma unroll
                        for (int k = 0; k < 2; k++) h2[k] = (u3 ? h4[k + 2] : h4[k]) + __shfl_xor_sync(~0u, u3 ? h4[k] : h4[k + 2], 8);
                        const float h1 = (u2 ? h2[1] : h2[0]) + __shfl_xor_sync(~0u, u2 ? h2[0] : h2[1], 4);
                        stsf(LRED + (warp * 32 + 8 * (g >> 1) + 2 * q + (g & 1)) * 4, h1);
                    }
                    if (tile == 1) {
                        asm volatile("bar.sync 3, 128;" ::: "memory");
                        if (wq == 0) {
                            float l0 = 0.f, l1 = 0.f;
#pragma unroll
                            for (int w = 0; w < 4; w++) { l0 += ldsf(LRED + (w * 32 + lane) * 4); l1 += ldsf(LRED + ((w + 4) * 32 + lane) * 4); }
                            const float l = l0 * ldsf(ALPHA + lane * 4) + l1;
                            const float mf = ldsf(MRUN + 256 + lane * 4);
                            if ((lane >> 4) == (int)rank) {
                                asm volatile("st.shared.v2.f32 [%0], {%1,%2};" ::"r"(OST + (lane & 15) * 8), "f"(mf), "f"(l) : "memory");
                            } else {
                                mbar_wait(BAR(B_PEER0));
                                st_async2(mapa(PST + (lane & 15) * 8, rank ^ 1), mf, l, mapa(BAR(B_XST), rank ^ 1));
                            }
                            __syncwarp();
                            if (lane == 0) mbar_arrive(BAR(B_XST));
                        }
                    }
                }
                if (tile == 0 && wg == 0) {
                    wg_wait0();
                    __syncwarp();
                    if (lane == 0) {
                        mbar_arrive(BAR(B_KV0FREE));
                        asm volatile("mbarrier.arrive.relaxed.cluster.shared::cluster.b64 _, [%0];" ::"r"(mapa(BAR(B_PEER0), rank ^ 1)) : "memory");
                    }
                    TS0(9);
                }
            }
            mbar_wait(BAR(B_PEER0));
            {
                const uint32_t rx = mapa(sb + OFF_XCH + t * 16, rank ^ 1), rb = mapa(BAR(B_XCH), rank ^ 1);
                asm volatile("wgmma.wait_group.sync.aligned 3;" ::: "memory");
                reg_fence(o[0]);
                st_async4(rx, pack_bf16(o[0][8], o[0][9]), pack_bf16(o[0][10], o[0][11]), pack_bf16(o[0][12], o[0][13]), pack_bf16(o[0][14], o[0][15]), rb);
                asm volatile("wgmma.wait_group.sync.aligned 2;" ::: "memory");
                reg_fence(o[1]);
                st_async4(rx + 4096, pack_bf16(o[1][8], o[1][9]), pack_bf16(o[1][10], o[1][11]), pack_bf16(o[1][12], o[1][13]), pack_bf16(o[1][14], o[1][15]), rb);
                asm volatile("wgmma.wait_group.sync.aligned 1;" ::: "memory");
                reg_fence(o[2]);
                st_async4(rx + 8192, pack_bf16(o[2][8], o[2][9]), pack_bf16(o[2][10], o[2][11]), pack_bf16(o[2][12], o[2][13]), pack_bf16(o[2][14], o[2][15]), rb);
                wg_wait0();
                reg_fence(o[3]);
                st_async4(rx + 12288, pack_bf16(o[3][8], o[3][9]), pack_bf16(o[3][10], o[3][11]), pack_bf16(o[3][12], o[3][13]), pack_bf16(o[3][14], o[3][15]), rb);
            }
            TS0(11);
            mbar_wait(BAR(B_XST));
            float ca[4], cb[4];
#pragma unroll
            for (int k = 0; k < 4; k++) {
                const int n = 8 * (k >> 1) + 2 * q + (k & 1);
                const float2 so = ldsf2(OST + n * 8), sp = ldsf2(PST + n * 8);
                const float mx = fmaxf(so.x, sp.x);
                ca[k] = ex2(so.x - mx);
                cb[k] = ex2(sp.x - mx);
            }
#pragma unroll
            for (int mt = 0; mt < 4; mt++) {
                o[mt][0] *= ca[0]; o[mt][1] *= ca[1]; o[mt][2] *= ca[0]; o[mt][3] *= ca[1];
                o[mt][4] *= ca[2]; o[mt][5] *= ca[3]; o[mt][6] *= ca[2]; o[mt][7] *= ca[3];
            }
            if (warp == 0) {
                const float2 so = ldsf2(OST + (lane & 15) * 8), sp = ldsf2(PST + (lane & 15) * 8);
                const float mx = fmaxf(so.x, sp.x);
                const float l = so.y * ex2(so.x - mx) + sp.y * ex2(sp.x - mx);
                const float ln = __shfl_down_sync(~0u, l, 1), mn = __shfl_down_sync(~0u, mx, 1);
                if (lane < 16 && (lane & 1) == 0) put4(&g_stat[((rank * 4 + (lane >> 2)) * 64 + (i >> 1)) * 2 + ((lane >> 1) & 1)], mx, l, mn, ln, tag);
            }
            const uint32_t keep = (g == 0) ? 0xFFFEFFFEu : 0xFFFFFFFFu;
            const uint32_t tg = (g == 0) ? ((ep & 1u) ? 0u : 0x00010001u) : 0u;
            const int hl = lane & 15, mi2 = lane >> 4;
            mbar_wait(BAR(B_XCH));
            TS0(46);
#pragma unroll
            for (int mt = 0; mt < 4; mt++) {
                const uint4 r = lds128(sb + OFF_XCH + mt * 4096 + t * 16);
                const uint32_t lo0 = (pack_bf16(o[mt][0] + cb[0] * bf_lo(r.x), o[mt][1] + cb[1] * bf_hi(r.x)) & keep) | tg;
                const uint32_t hi0 = (pack_bf16(o[mt][2] + cb[0] * bf_lo(r.y), o[mt][3] + cb[1] * bf_hi(r.y)) & keep) | tg;
                const uint32_t lo1 = (pack_bf16(o[mt][4] + cb[2] * bf_lo(r.z), o[mt][5] + cb[3] * bf_hi(r.z)) & keep) | tg;
                const uint32_t hi1 = (pack_bf16(o[mt][6] + cb[2] * bf_lo(r.w), o[mt][7] + cb[3] * bf_hi(r.w)) & keep) | tg;
                const uint32_t row = sb + OFF_STG + (wg * 2 + (mt >> 1)) * 4096 + hl * 256;
                const int ch = (mt & 1) * 8 + wq * 2 + mi2;
                stsm4t(row + ((ch ^ (hl & 7)) << 4), lo0, lo1, hi0, hi1);
            }
            fence_async_smem();
            if (wg == 0) asm volatile("bar.sync 2, 128;" ::: "memory"); else asm volatile("bar.sync 3, 128;" ::: "memory");
            if (warp == 4) TS(47);
            if (wq == 0 && lane == 0) {
                bulk_s2g(&g_part[i * 1024 + wg * 512], sb + OFF_STG + wg * 8192, 8192);
                asm volatile("cp.async.bulk.commit_group;" ::: "memory");
                asm volatile("cp.async.bulk.wait_group 0;" ::: "memory");
                if (atomicAdd(reinterpret_cast<unsigned int*>(smem + OFF_MISC + 236), 1u) == 1u) red_cnt(&g_sync[bb * 32 + 1]);
            }
            TS0(12);
        }
        mbar_wait(BAR(B_CLR2));
        const uint32_t SCR = sb + OFF_SCR;
        {
            const int b = warp >> 1;
            const uint32_t ptag = par;
            const int pi = lane >> 3, v = (warp & 1) * 8 + (lane & 7);
            const uint4* sp = &g_stat[((hh >> 2) * 64 + b * 16 + (lane & 15)) * 2 + ((hh >> 1) & 1)];
            const uint4* src = &g_part[(2 * (b * 16 + pi) + (hh >> 4)) * 1024 + (jj * 16 + (hh & 15)) * 16 + v];
            float acc[8];
            int it = 0;
            bool ok;
            mbar_wait_n(BAR(B_WUV), 4);
            gemv_y_load(afr);
            float wi;
            {
                const unsigned int t_stat = lds32(MISC + 232) - STAT_LEAD;
#pragma unroll 1
                while ((int)(gtimer_lo() - t_stat) < 0 && ++it < SPIN_LIMIT) {}
                const float4 su = get4(sp, true, tag);
                const float mi = (hh & 1) ? su.z : su.x, li = (hh & 1) ? su.w : su.y;
                float mx = mi;
#pragma unroll
                for (int of = 8; of; of >>= 1) mx = fmaxf(mx, __shfl_xor_sync(~0u, mx, of));
                wi = ex2(mi - mx);
                float L = wi * li;
#pragma unroll
                for (int of = 8; of; of >>= 1) L += __shfl_xor_sync(~0u, L, of);
                wi = __fdividef(wi, L);
            }
            float w4[4];
#pragma unroll
            for (int k = 0; k < 4; k++) w4[k] = __shfl_sync(~0u, wi, 4 * k + pi);
            mbar_wait(BAR(B_G4));
            it = 0;
#pragma unroll 1
            do {
                uint4 r[4];
#pragma unroll
                for (int k = 0; k < 4; k++) r[k] = ld128(src + (size_t)k * 8 * 1024);
                ok = true;
#pragma unroll
                for (int k = 0; k < 8; k++) acc[k] = 0.f;
#pragma unroll
                for (int k = 0; k < 4; k++) {
                    const float w = w4[k];
                    ok = ok & ((r[k].x & 1u) == ptag);
                    acc[0] += w * bf_lo(r[k].x); acc[1] += w * bf_hi(r[k].x);
                    acc[2] += w * bf_lo(r[k].y); acc[3] += w * bf_hi(r[k].y);
                    acc[4] += w * bf_lo(r[k].z); acc[5] += w * bf_hi(r[k].z);
                    acc[6] += w * bf_lo(r[k].w); acc[7] += w * bf_hi(r[k].w);
                }
            } while (!__all_sync(~0u, ok) && ++it < SPIN_LIMIT);
            {
                const bool u4 = lane & 16, u3 = lane & 8;
                float h4[4], h2[2];
#pragma unroll
                for (int k = 0; k < 4; k++) h4[k] = (u4 ? acc[k + 4] : acc[k]) + __shfl_xor_sync(~0u, u4 ? acc[k] : acc[k + 4], 16);
#pragma unroll
                for (int k = 0; k < 2; k++) h2[k] = (u3 ? h4[k + 2] : h4[k]) + __shfl_xor_sync(~0u, u3 ? h4[k] : h4[k + 2], 8);
                const int ch = v ^ (hh & 7);
                sts32(ACT + b * 272 + (ch * 8 + (u4 ? 4 : 0) + (u3 ? 2 : 0)) * 2, pack_bf16(h2[0], h2[1]));
            }
            bar_main();
            TS0(14);
        }
        gemv_y_put(afr, &g_C[i * 128], ACT, tag);
        TS0(17);
        mbar_wait_n(BAR(B_WO), 4);
        {
            const int blk = lane >> 3, r8 = lane & 7;
            const uint32_t wb = sb + OFF_X + warp * 4096 + ((blk >> 1) * 8 + r8) * 128;
#pragma unroll
            for (int mt = 0; mt < 4; mt++) {
                const uint32_t co = ((2 * mt + (blk & 1)) ^ r8) << 4;
                ldsm4t(afr[2 * mt], wb + co);
                ldsm4t(afr[2 * mt + 1], wb + 16 * 128 + co);
            }
        }
        if (warp == 0) {
            const float4 a = get4sum4(&g_C[hh * 4 * 128 + jj * 32 + lane], 128, tag);
            sts_frag(ACTB, 80, (t >> 4) * 16 + vrr, vb0, a.x, a.y, a.z, a.w);
        }
        bar_main();
        TS0(16);
        {
            uint32_t b[4];
            ldsm4(b, ACTB + (lane & 3) * 80 + (lane >> 3) * 16);
            uint32_t px[4], py[4];
#pragma unroll
            for (int mt = 0; mt < 4; mt++) {
                float d[4] = {0.f, 0.f, 0.f, 0.f};
                mma16816(d, afr[2 * mt], b[0], b[1]);
                mma16816(d, afr[2 * mt + 1], b[2], b[3]);
                px[mt] = (pack_bf16(d[0], d[1]) & ~1u) | par;
                py[mt] = pack_bf16(d[2], d[3]);
            }
            if (q < 2) {
                uint2* dst = &g_O[i * 512 + warp * 64 + g * 2 + q];
#pragma unroll
                for (int mt = 0; mt < 4; mt++) st64(dst + mt * 16, px[mt], py[mt]);
            }
            TS0(18);
        }
        const int V = i * 4 + (t & 3);
        const int vm = (V >> 4) * 16 + ((V & 15) >> 1), vb = (V & 1) * 2;
        float4 x1 = make_float4(0.f, 0.f, 0.f, 0.f);
        {
            mbar_wait(BAR(B_MODV));
            const float4 r = reduce16(g_O, 128, par, G6ADELAY);
            if (t < 4) {
                const float4 x0 = ldsf4(MISC + 32 + t * 16), ga = ldsf4(MISC + 96 + t * 16);
                x1 = make_float4(x0.x + ga.x * r.x, x0.y + ga.y * r.y, x0.z + ga.z * r.z, x0.w + ga.w * r.w);
                put2(&g_X1[i * 8 + t], x1.x, x1.y, x1.z, x1.w, par);
            }
            TS0(19);
        }
        if (i < NFFN) {
            float4 mv[4];
#pragma unroll
            for (int k = 0; k < 4; k++) {
                uint4 u = lds128(sb + OFF_SBCB + (t + 256 * k) * 16);
                int it = 0;
                while ((u.x & 3u) != tag && ++it < SPIN_LIMIT) u = ld128(&g_M[512 + t + 256 * k]);
                mv[k] = as_f4(u);
            }
            mbar_wait_n(BAR(B_W1), 4);
            {
                const int blk = lane >> 3, r8 = lane & 7;
                const uint32_t w1r = sb + OFF_Z + (warp * 64 + (blk >> 1) * 8 + r8) * 32 + (((blk & 1) ^ ((r8 >> 2) & 1)) << 4);
                const uint32_t w2r = sb + OFF_W2 + warp * 2048 + ((blk >> 1) * 8 + r8) * 128;
#pragma unroll
                for (int k = 0; k < 4; k++) {
                    ldsm4t(afr[k], w1r + k * 512);
                    ldsm4t(afr[4 + k], w2r + (((2 * k + (blk & 1)) ^ r8) << 4));
                }
            }
            TS0(21);
            uint2 ua, ub;
            {
                int it = 0;
#pragma unroll 1
                do { ua = ld64(&g_X1[(t >> 2) * 8 + (t & 3)]); ub = ld64(&g_X1[(t >> 2) * 8 + (t & 3) + 512]); } while (!__all_sync(~0u, (((ua.x ^ par) | (ub.x ^ par)) & 1u) == 0) && ++it < SPIN_LIMIT);
            }
            const float4 a = as_f4(ua), b = as_f4(ub);
            float s0 = (a.x + a.z) + (b.x + b.z), s1 = (a.y + a.w) + (b.y + b.w);
            float q0 = (a.x * a.x + a.z * a.z) + (b.x * b.x + b.z * b.z), q1 = (a.y * a.y + a.w * a.w) + (b.y * b.y + b.w * b.w);
#pragma unroll
            for (int of = 2; of <= 16; of <<= 1) {
                s0 += __shfl_xor_sync(~0u, s0, of); s1 += __shfl_xor_sync(~0u, s1, of);
                q0 += __shfl_xor_sync(~0u, q0, of); q1 += __shfl_xor_sync(~0u, q1, of);
            }
            const uint32_t ST = SCR + 1024, ACT2 = SCR + 4096;
            if (lane < 2) stsf4(ST + (warp * 2 + lane) * 16, make_float4(s0, q0, s1, q1));
            bar_main();
            TS0(20);
            float4 tot = make_float4(0.f, 0.f, 0.f, 0.f);
#pragma unroll
            for (int w = 0; w < 8; w++) add4(tot, ldsf4(ST + (w * 2 + (t & 1)) * 16));
            const float mean0 = tot.x * (1.f / 512.f), mean1 = tot.z * (1.f / 512.f);
            const float r0 = rsqrtf(fmaxf(tot.y * (1.f / 512.f) - mean0 * mean0, 0.f) + 1e-5f);
            const float r1 = rsqrtf(fmaxf(tot.w * (1.f / 512.f) - mean1 * mean1, 0.f) + 1e-5f);
            const int m0 = (t >> 4) * 16 + vrr;
            sts_frag(ACT2, 1040, m0, vb0, (a.x - mean0) * r0 * (1.f + mv[2].x) + mv[0].x, (a.y - mean1) * r1 * (1.f + mv[2].y) + mv[0].y,
                     (a.z - mean0) * r0 * (1.f + mv[2].z) + mv[0].z, (a.w - mean1) * r1 * (1.f + mv[2].w) + mv[0].w);
            sts_frag(ACT2, 1040, m0 + 256, vb0, (b.x - mean0) * r0 * (1.f + mv[3].x) + mv[1].x, (b.y - mean1) * r1 * (1.f + mv[3].y) + mv[1].y,
                     (b.z - mean0) * r0 * (1.f + mv[3].z) + mv[1].z, (b.w - mean1) * r1 * (1.f + mv[3].w) + mv[1].w);
            bar_main();
            float d[4] = {0.f, 0.f, 0.f, 0.f};
            {
                const uint32_t brow = ACT2 + (lane & 3) * 1040 + (warp * 64 + (lane >> 3) * 8) * 2;
                uint32_t b0[4], b1[4];
                ldsm4(b0, brow);
                ldsm4(b1, brow + 64);
                float e[4] = {0.f, 0.f, 0.f, 0.f};
                mma16816(d, afr[0], b0[0], b0[1]);
                mma16816(e, afr[1], b0[2], b0[3]);
                mma16816(d, afr[2], b1[0], b1[1]);
                mma16816(e, afr[3], b1[2], b1[3]);
                d[0] += e[0]; d[1] += e[1]; d[2] += e[2]; d[3] += e[3];
            }
            const uint32_t HR = SCR + 2048;
            if (q < 2) {
                const uint32_t a0 = HR + (warp * 64 + (2 * q) * 16 + (g >> 1) * 4 + (g & 1)) * 4;
                stsf(a0, d[0]); stsf(a0 + 64, d[1]); stsf(a0 + 8, d[2]); stsf(a0 + 72, d[3]);
            }
            bar_main();
            float4 hs = ldsf4(HR + ((g & 3) * 16 + q * 4) * 4);
#pragma unroll
            for (int w = 1; w < 8; w++) add4(hs, ldsf4(HR + (w * 64 + (g & 3) * 16 + q * 4) * 4));
            const uint32_t b0r = pack_bf16(fmaxf(hs.x, 0.f), fmaxf(hs.y, 0.f)), b1r = pack_bf16(fmaxf(hs.z, 0.f), fmaxf(hs.w, 0.f));
            TS0(22);
            uint32_t px[4], py[4];
#pragma unroll
            for (int mt = 0; mt < 4; mt++) {
                float e[4] = {0.f, 0.f, 0.f, 0.f};
                mma16816(e, afr[4 + mt], b0r, b1r);
                px[mt] = (pack_bf16(e[0], e[1]) & ~1u) | par;
                py[mt] = pack_bf16(e[2], e[3]);
            }
            if (q < 2) {
                uint2* dst = &g_F[i * 512 + warp * 64 + g * 2 + q];
#pragma unroll
                for (int mt = 0; mt < 4; mt++) st64(dst + mt * 16, px[mt], py[mt]);
            }
            TS0(23);
        }
        {
            const float4 r = reduce16(g_F, NFFN, par, i < NFFN ? HOPDELAY : FFNDELAY);
            if (t < 4) {
                const float4 gb = ldsf4(MISC + 96 + 64 + t * 16);
                p.out[vb * 512 + vm] = __float2bfloat16_rn(x1.x + gb.x * r.x);
                p.out[(vb + 1) * 512 + vm] = __float2bfloat16_rn(x1.y + gb.y * r.y);
                p.out[vb * 512 + vm + 8] = __float2bfloat16_rn(x1.z + gb.z * r.z);
                p.out[(vb + 1) * 512 + vm + 8] = __float2bfloat16_rn(x1.w + gb.w * r.w);
            }
            if (i == 0 && t < NSYNC) g_sync[t * 32] = ep + 1u;
            TS0(24);
        }
    }
}

typedef CUresult (*EncodeFn)(CUtensorMap*, CUtensorMapDataType, cuuint32_t, void*, const cuuint64_t*, const cuuint64_t*, const cuuint32_t*,
                             const cuuint32_t*, CUtensorMapInterleave, CUtensorMapSwizzle, CUtensorMapL2promotion, CUtensorMapFloatOOBfill);

void make_map(EncodeFn enc, CUtensorMap* m, const void* base, int rank, const cuuint64_t* dims, const cuuint64_t* strides, const cuuint32_t* box,
              CUtensorMapSwizzle sw) {
    cuuint32_t es[3] = {1, 1, 1};
    CUresult r = enc(m, CU_TENSOR_MAP_DATA_TYPE_BFLOAT16, rank, const_cast<void*>(base), dims, strides, box, es, CU_TENSOR_MAP_INTERLEAVE_NONE, sw,
                     CU_TENSOR_MAP_L2_PROMOTION_NONE, CU_TENSOR_MAP_FLOAT_OOB_FILL_NONE);
    if (r != CUDA_SUCCESS) fprintf(stderr, "cuTensorMapEncodeTiled failed: %d\n", (int)r);
}
void map2d(EncodeFn enc, CUtensorMap* m, const void* base, uint64_t rows, uint64_t cols, uint32_t boxr, uint32_t boxc, CUtensorMapSwizzle sw) {
    cuuint64_t dims[2] = {cols, rows};
    cuuint64_t strides[1] = {cols * 2};
    cuuint32_t box[2] = {boxc, boxr};
    make_map(enc, m, base, 2, dims, strides, box, sw);
}
void map3d(EncodeFn enc, CUtensorMap* m, const void* base, uint64_t rows, uint32_t boxr, uint32_t boxb) {
    cuuint64_t dims[3] = {64, rows, 8};
    cuuint64_t strides[2] = {1024, 128};
    cuuint32_t box[3] = {64, boxr, boxb};
    make_map(enc, m, base, 3, dims, strides, box, CU_TENSOR_MAP_SWIZZLE_128B);
}

}

extern "C" void kernel_launch(void* const* d_in, const int* in_sizes, int n_in, void* d_out, int out_size) {
    (void)in_sizes; (void)n_in; (void)out_size;
    static EncodeFn enc = nullptr;
    static void* qabs_ptr = nullptr;
    static bool fits = false;
    if (!enc) {
        void* fn = nullptr;
        cudaDriverEntryPointQueryResult st;
        cudaGetDriverEntryPoint("cuTensorMapEncodeTiled", &fn, cudaEnableDefault, &st);
        enc = (EncodeFn)fn;
        cudaFuncSetAttribute(fused_kernel, cudaFuncAttributeMaxDynamicSharedMemorySize, SMEM_BYTES);
        cudaGetSymbolAddress(&qabs_ptr, g_qabs);
        cudaLaunchConfig_t cfg = {};
        cfg.gridDim = dim3(NCTA);
        cfg.blockDim = dim3(NTHREADS);
        cfg.dynamicSmemBytes = SMEM_BYTES;
        cudaLaunchAttribute at[1];
        at[0].id = cudaLaunchAttributeClusterDimension;
        at[0].val.clusterDim.x = 2; at[0].val.clusterDim.y = 1; at[0].val.clusterDim.z = 1;
        cfg.attrs = at;
        cfg.numAttrs = 1;
        int nclusters = 0;
        if (cudaOccupancyMaxActiveClusters(&nclusters, fused_kernel, &cfg) != cudaSuccess) { (void)cudaGetLastError(); nclusters = NCTA / 2; }
        fits = nclusters >= NCTA / 2;
        if (!fits) fprintf(stderr, "fused_kernel: only %d of %d clusters can be resident on this device\n", nclusters, NCTA / 2);
    }
    if (!enc || !fits) return;
    Params p;
    map2d(enc, &p.kv, d_in[1], 16384, 512, 64, 64, CU_TENSOR_MAP_SWIZZLE_128B);
    map2d(enc, &p.wq, d_in[2], 512, 4096, 64, 64, CU_TENSOR_MAP_SWIZZLE_128B);
    map2d(enc, &p.wuk, d_in[3], 512, 4096, 64, 64, CU_TENSOR_MAP_SWIZZLE_128B);
    map2d(enc, &p.wuv, d_in[4], 512, 4096, 64, 64, CU_TENSOR_MAP_SWIZZLE_128B);
    map3d(enc, &p.wo, d_in[5], 4096, 32, 2);
    map2d(enc, &p.w1, d_in[7], 512, 1376, 256, 16, CU_TENSOR_MAP_SWIZZLE_32B);
    map3d(enc, &p.w2, d_in[8], 1376, 16, 4);
    map2d(enc, &p.wmod, d_in[10], 512, 3072, 256, 16, CU_TENSOR_MAP_SWIZZLE_32B);
    map3d(enc, &p.qabs, qabs_ptr, 128, 32, 4);
    map2d(enc, &p.wmoda, d_in[10], 512, 3072, 128, 16, CU_TENSOR_MAP_SWIZZLE_32B);
    p.x = (const __nv_bfloat16*)d_in[0];
    p.c = (const __nv_bfloat16*)d_in[9];
    p.out = (__nv_bfloat16*)d_out;
    fused_kernel<<<NCTA, NTHREADS, SMEM_BYTES, cudaStreamPerThread>>>(p);
}
```

```cpp
#include <cuda_runtime.h>
#include <cuda_bf16.h>
#include <cuda.h>
#include <stdint.h>
#include <stdio.h>

namespace {

constexpr int NCTA = 128;
constexpr int NTHREADS = 320;
constexpr int NFFN = 86;
#define WINDOW 5
#define DT_0 500
#define DT_F 340
#define DT_S 325
#define DT_T 320
#define DT_T2 300
#define QK_EARLY 4
#define GATE_NS 3600
#define STAT_LEAD 200
#define G6ADELAY 450
#define HOPDELAY 300
#define FFNDELAY 2300

constexpr uint32_t OFF_KV = 0;
constexpr uint32_t OFF_X = 131072;
constexpr uint32_t OFF_Y = 163840;
constexpr uint32_t OFF_Z = 196608;
constexpr uint32_t OFF_P = 212992;
constexpr uint32_t OFF_S = 221184;
constexpr uint32_t OFF_ACT = 225344;
constexpr uint32_t OFF_RED = 227648;
constexpr uint32_t OFF_BAR = 229696;
constexpr uint32_t OFF_MISC = 230208;
constexpr uint32_t SMEM_BYTES = 230720;
constexpr uint32_t OFF_STG = OFF_KV;
constexpr uint32_t OFF_XCH = OFF_KV + 16384;
constexpr uint32_t OFF_W2 = OFF_KV + 32768;
constexpr uint32_t OFF_SBCB = OFF_KV + 49152;
constexpr uint32_t OFF_SCR = OFF_KV + 65536;

enum {
    B_WQ = 0,
    B_WUK = 4,
    B_KV = 8,
    B_MOD = 24,
    B_WUV = 26,
    B_WO = 30,
    B_W1 = 34,
    B_W2 = 36,
    B_QABS = 38,
    B_YFREE = 39,
    B_XFREE = 40,
    B_ZFREE = 41,
    B_KV0FREE = 42,
    B_P3 = 43,
    B_CLR2 = 44,
    B_MODV = 45,
    B_WA = 46,
    B_EP = 47,
    B_PEER0 = 48,
    B_XCH = 49,
    B_G4 = 50,
    B_XST = 51,
    B_COUNT = 52
};

struct alignas(64) Params {
    CUtensorMap kv, wq, wuk, wuv, wo, w1, w2, wmod, qabs, wmoda;
    const __nv_bfloat16* x;
    const __nv_bfloat16* c;
    __nv_bfloat16* out;
};

__device__ __align__(128) uint4 g_H[128 * 32];
__device__ __align__(128) uint4 g_Q[128 * 128];
__device__ __align__(128) __nv_bfloat16 g_qabs[4 * 32 * 512];
__device__ __align__(128) uint4 g_part[128 * 4 * 16 * 16];
__device__ __align__(128) uint4 g_stat[8 * 64 * 2];
__device__ __align__(128) uint4 g_C[128 * 128];
__device__ __align__(128) uint2 g_O[128 * 512];
__device__ __align__(128) uint2 g_X1[128 * 8];
__device__ __align__(128) uint2 g_F[NFFN * 512];
__device__ __align__(128) uint4 g_M[4 * 512];
constexpr int NSYNC = 8;
__device__ __align__(128) unsigned int g_sync[NSYNC * 32];

__device__ __forceinline__ uint32_t smem_u32(const void* p) { return (uint32_t)__cvta_generic_to_shared(p); }
__device__ __forceinline__ void mbar_init(uint32_t bar, int cnt) { asm volatile("mbarrier.init.shared::cta.b64 [%0], %1;" ::"r"(bar), "r"(cnt) : "memory"); }
__device__ __forceinline__ void mbar_expect_tx(uint32_t bar, uint32_t bytes) { asm volatile("mbarrier.arrive.expect_tx.shared::cta.b64 _, [%0], %1;" ::"r"(bar), "r"(bytes) : "memory"); }
__device__ __forceinline__ void mbar_arrive(uint32_t bar) { asm volatile("mbarrier.arrive.shared::cta.b64 _, [%0];" ::"r"(bar) : "memory"); }
constexpr int SPIN_LIMIT = 1 << 20;
__device__ __forceinline__ void mbar_wait(uint32_t bar) {
    asm volatile("{\n.reg .pred p;\n.reg .u32 n;\nmov.u32 n, 0;\n"
                 "LW:\nmbarrier.try_wait.parity.shared::cta.b64 p, [%0], 0;\n@p bra LD;\n"
                 "add.u32 n, n, 1;\nsetp.lt.u32 p, n, 262144;\n@p bra LW;\nLD:\n}" ::"r"(bar) : "memory");
}
__device__ __forceinline__ void mbar_wait_n(uint32_t bar, int n) {
#pragma unroll 1
    for (int k = 0; k < n; k++) mbar_wait(bar + k * 8);
}
__device__ __forceinline__ void bar_main() { asm volatile("bar.sync 1, 256;" ::: "memory"); }
__device__ __forceinline__ void fence_async_smem() { asm volatile("fence.proxy.async.shared::cta;" ::: "memory"); }

__device__ __forceinline__ uint4 ld128(const uint4* p) {
    uint4 v;
    asm volatile("{\n.reg .b128 t;\n.reg .b64 lo, hi;\nld.relaxed.gpu.global.b128 t, [%4];\nmov.b128 {lo, hi}, t;\nmov.b64 {%0,%1}, lo;\nmov.b64 {%2,%3}, hi;\n}"
                 : "=r"(v.x), "=r"(v.y), "=r"(v.z), "=r"(v.w) : "l"(p) : "memory");
    return v;
}
__device__ __forceinline__ void st128(uint4* p, uint4 v) {
    asm volatile("{\n.reg .b128 t;\n.reg .b64 lo, hi;\nmov.b64 lo, {%1,%2};\nmov.b64 hi, {%3,%4};\nmov.b128 t, {lo, hi};\nst.relaxed.gpu.global.b128 [%0], t;\n}"
                 ::"l"(p), "r"(v.x), "r"(v.y), "r"(v.z), "r"(v.w) : "memory");
}
__device__ __forceinline__ uint4 ldnc128_if(const void* p, bool c) {
    uint4 v;
    asm volatile("{\n.reg .pred p;\nsetp.ne.u32 p, %5, 0;\nmov.u32 %0, 0;\nmov.u32 %1, 0;\nmov.u32 %2, 0;\nmov.u32 %3, 0;\n@p ld.global.nc.v4.u32 {%0,%1,%2,%3}, [%4];\n}"
                 : "=r"(v.x), "=r"(v.y), "=r"(v.z), "=r"(v.w) : "l"(p), "r"((uint32_t)c));
    return v;
}
__device__ __forceinline__ uint32_t ldnc32(const void* p) { uint32_t v; asm volatile("ld.global.nc.u32 %0, [%1];" : "=r"(v) : "l"(p)); return v; }
__device__ __forceinline__ uint32_t ldnc16(const void* p) { uint32_t v; asm volatile("ld.global.nc.u16 %0, [%1];" : "=r"(v) : "l"(p)); return v; }
__device__ __forceinline__ unsigned int ld_epoch(const unsigned int* p) { unsigned int v; asm volatile("ld.relaxed.gpu.global.u32 %0, [%1];" : "=r"(v) : "l"(p)); return v; }
__device__ __forceinline__ void put4(uint4* p, float a, float b, float c, float d, uint32_t tag) {
    st128(p, make_uint4((__float_as_uint(a) & ~3u) | tag, __float_as_uint(b), __float_as_uint(c), __float_as_uint(d)));
}
__device__ __forceinline__ float4 as_f4(uint4 v) {
    return make_float4(__uint_as_float(v.x & ~3u), __uint_as_float(v.y), __uint_as_float(v.z), __uint_as_float(v.w));
}
__device__ __forceinline__ void add4(float4& a, const float4& b) { a.x += b.x; a.y += b.y; a.z += b.z; a.w += b.w; }
__device__ __forceinline__ float4 get4(const uint4* p, bool act, uint32_t tag) {
    uint4 v = make_uint4(tag, 0, 0, 0);
    int it = 0;
#pragma unroll 1
    do { if (act) v = ld128(p); } while (!__all_sync(~0u, (v.x & 3u) == tag) && ++it < SPIN_LIMIT);
    return as_f4(v);
}
__device__ __forceinline__ uint2 ld64(const uint2* p) { uint2 v; asm volatile("{\n.reg .b64 t;\nld.relaxed.gpu.global.b64 t, [%2];\nmov.b64 {%0,%1}, t;\n}" : "=r"(v.x), "=r"(v.y) : "l"(p) : "memory"); return v; }
__device__ __forceinline__ void st64(uint2* p, uint32_t x, uint32_t y) { asm volatile("{\n.reg .b64 t;\nmov.b64 t, {%1,%2};\nst.relaxed.gpu.global.b64 [%0], t;\n}" ::"l"(p), "r"(x), "r"(y) : "memory"); }
__device__ __forceinline__ uint32_t pack_bf16(float lo, float hi);
__device__ __forceinline__ void put2(uint2* p, float a, float b, float c, float d, uint32_t par) { st64(p, (pack_bf16(a, b) & ~1u) | par, pack_bf16(c, d)); }
__device__ __forceinline__ float4 as_f4(uint2 v) {
    return make_float4(__uint_as_float(v.x << 16), __uint_as_float(v.x & 0xffff0000u), __uint_as_float(v.y << 16), __uint_as_float(v.y & 0xffff0000u));
}
__device__ __forceinline__ float4 get4sum4(const uint4* p0, int stride, uint32_t tag) {
    uint4 u0, u1, u2, u3;
    int it = 0;
#pragma unroll 1
    do { u0 = ld128(p0); u1 = ld128(p0 + stride); u2 = ld128(p0 + 2 * stride); u3 = ld128(p0 + 3 * stride); }
    while (!__all_sync(~0u, ((u0.x ^ tag) & 3u) == 0 && ((u1.x ^ tag) & 3u) == 0 && ((u2.x ^ tag) & 3u) == 0 && ((u3.x ^ tag) & 3u) == 0) && ++it < SPIN_LIMIT);
    float4 a = as_f4(u0), b = as_f4(u2);
    add4(a, as_f4(u1));
    add4(b, as_f4(u3));
    add4(a, b);
    return a;
}
__device__ __forceinline__ uint32_t pack_bf16(float lo, float hi) {
    uint32_t r;
    asm("cvt.rn.bf16x2.f32 %0, %1, %2;" : "=r"(r) : "f"(hi), "f"(lo));
    return r;
}
__device__ __forceinline__ float bf_lo(uint32_t u) { return __uint_as_float(u << 16); }
__device__ __forceinline__ float bf_hi(uint32_t u) { return __uint_as_float(u & 0xffff0000u); }
__device__ __forceinline__ float ex2(float x) { float y; asm("ex2.approx.ftz.f32 %0, %1;" : "=f"(y) : "f"(x)); return y; }

__device__ __forceinline__ void ldsm4(uint32_t (&r)[4], uint32_t addr) {
    asm volatile("ldmatrix.sync.aligned.m8n8.x4.shared.b16 {%0,%1,%2,%3}, [%4];" : "=r"(r[0]), "=r"(r[1]), "=r"(r[2]), "=r"(r[3]) : "r"(addr) : "memory");
}
__device__ __forceinline__ void ldsm4t(uint32_t (&r)[4], uint32_t addr) {
    asm volatile("ldmatrix.sync.aligned.m8n8.x4.trans.shared.b16 {%0,%1,%2,%3}, [%4];" : "=r"(r[0]), "=r"(r[1]), "=r"(r[2]), "=r"(r[3]) : "r"(addr) : "memory");
}
__device__ __forceinline__ void stsm4t(uint32_t addr, uint32_t r0, uint32_t r1, uint32_t r2, uint32_t r3) {
    asm volatile("stmatrix.sync.aligned.m8n8.x4.trans.shared.b16 [%0], {%1,%2,%3,%4};" ::"r"(addr), "r"(r0), "r"(r1), "r"(r2), "r"(r3) : "memory");
}
__device__ __forceinline__ void mma16816(float (&d)[4], const uint32_t (&a)[4], uint32_t b0, uint32_t b1) {
    asm volatile("mma.sync.aligned.m16n8k16.row.col.f32.bf16.bf16.f32 {%0,%1,%2,%3}, {%4,%5,%6,%7}, {%8,%9}, {%0,%1,%2,%3};"
                 : "+f"(d[0]), "+f"(d[1]), "+f"(d[2]), "+f"(d[3]) : "r"(a[0]), "r"(a[1]), "r"(a[2]), "r"(a[3]), "r"(b0), "r"(b1));
}
__device__ __forceinline__ void sts32(uint32_t a, uint32_t v) { asm volatile("st.shared.b32 [%0], %1;" ::"r"(a), "r"(v) : "memory"); }
__device__ __forceinline__ void sts16(uint32_t a, float v) {
    __nv_bfloat16 h = __float2bfloat16_rn(v);
    asm volatile("st.shared.b16 [%0], %1;" ::"r"(a), "h"(*reinterpret_cast<unsigned short*>(&h)) : "memory");
}
__device__ __forceinline__ void stsf(uint32_t a, float v) { asm volatile("st.shared.f32 [%0], %1;" ::"r"(a), "f"(v) : "memory"); }
__device__ __forceinline__ void stsf4(uint32_t a, float4 v) { asm volatile("st.shared.v4.f32 [%0], {%1,%2,%3,%4};" ::"r"(a), "f"(v.x), "f"(v.y), "f"(v.z), "f"(v.w) : "memory"); }
__device__ __forceinline__ uint32_t lds32(uint32_t a) { uint32_t v; asm volatile("ld.shared.b32 %0, [%1];" : "=r"(v) : "r"(a) : "memory"); return v; }
__device__ __forceinline__ float ldsf(uint32_t a) { float v; asm volatile("ld.shared.f32 %0, [%1];" : "=f"(v) : "r"(a) : "memory"); return v; }
__device__ __forceinline__ float2 ldsf2(uint32_t a) { float2 v; asm volatile("ld.shared.v2.f32 {%0,%1}, [%2];" : "=f"(v.x), "=f"(v.y) : "r"(a) : "memory"); return v; }
__device__ __forceinline__ float4 ldsf4(uint32_t a) { float4 v; asm volatile("ld.shared.v4.f32 {%0,%1,%2,%3}, [%4];" : "=f"(v.x), "=f"(v.y), "=f"(v.z), "=f"(v.w) : "r"(a) : "memory"); return v; }
__device__ __forceinline__ uint4 lds128(uint32_t a) { uint4 v; asm volatile("ld.shared.v4.b32 {%0,%1,%2,%3}, [%4];" : "=r"(v.x), "=r"(v.y), "=r"(v.z), "=r"(v.w) : "r"(a) : "memory"); return v; }

__device__ __forceinline__ void tma2d(uint32_t dst, const CUtensorMap* m, int c0, int c1, uint32_t bar, uint32_t bytes, uint64_t pol) {
    asm volatile("{\n.reg .pred p;\nelect.sync _|p, 0xffffffff;\n"
                 "@p mbarrier.arrive.expect_tx.shared::cta.b64 _, [%2], %6;\n"
                 "@p cp.async.bulk.tensor.2d.shared::cluster.global.mbarrier::complete_tx::bytes.L2::cache_hint [%0], [%1, {%3, %4}], [%2], %5;\n}"
                 ::"r"(dst), "l"(m), "r"(bar), "r"(c0), "r"(c1), "l"(pol), "r"(bytes) : "memory");
}
__device__ __forceinline__ void tma3d(uint32_t dst, const CUtensorMap* m, int c0, int c1, int c2, uint32_t bar, uint32_t bytes, uint64_t pol) {
    asm volatile("{\n.reg .pred p;\nelect.sync _|p, 0xffffffff;\n"
                 "@p mbarrier.arrive.expect_tx.shared::cta.b64 _, [%2], %7;\n"
                 "@p cp.async.bulk.tensor.3d.shared::cluster.global.mbarrier::complete_tx::bytes.L2::cache_hint [%0], [%1, {%3, %4, %5}], [%2], %6;\n}"
                 ::"r"(dst), "l"(m), "r"(bar), "r"(c0), "r"(c1), "r"(c2), "l"(pol), "r"(bytes) : "memory");
}
__device__ __forceinline__ void tma2d_na(uint32_t dst, const CUtensorMap* m, int c0, int c1, uint32_t bar, uint64_t pol) {
    asm volatile("{\n.reg .pred p;\nelect.sync _|p, 0xffffffff;\n"
                 "@p cp.async.bulk.tensor.2d.shared::cluster.global.mbarrier::complete_tx::bytes.L2::cache_hint [%0], [%1, {%3, %4}], [%2], %5;\n}"
                 ::"r"(dst), "l"(m), "r"(bar), "r"(c0), "r"(c1), "l"(pol) : "memory");
}
__device__ __forceinline__ uint32_t mapa(uint32_t addr, uint32_t rank) {
    uint32_t r;
    asm("mapa.shared::cluster.u32 %0, %1, %2;" : "=r"(r) : "r"(addr), "r"(rank));
    return r;
}
__device__ __forceinline__ void st_async4(uint32_t raddr, uint32_t a, uint32_t b, uint32_t c, uint32_t d, uint32_t rbar) {
    asm volatile("st.async.weak.shared::cluster.mbarrier::complete_tx::bytes.v4.b32 [%0], {%1,%2,%3,%4}, [%5];" ::"r"(raddr), "r"(a), "r"(b), "r"(c), "r"(d), "r"(rbar) : "memory");
}
__device__ __forceinline__ void st_async2(uint32_t raddr, float a, float b, uint32_t rbar) {
    asm volatile("st.async.weak.shared::cluster.mbarrier::complete_tx::bytes.v2.f32 [%0], {%1,%2}, [%3];" ::"r"(raddr), "f"(a), "f"(b), "r"(rbar) : "memory");
}
__device__ __forceinline__ void tma3d_mc(uint32_t dst, const CUtensorMap* m, int c0, int c1, int c2, uint32_t bar, uint32_t bytes) {
    asm volatile("{\n.reg .pred p;\nelect.sync _|p, 0xffffffff;\n"
                 "@p mbarrier.arrive.expect_tx.shared::cta.b64 _, [%2], %6;\n"
                 "@p cp.async.bulk.tensor.3d.shared::cluster.global.mbarrier::complete_tx::bytes.multicast::cluster [%0], [%1, {%3, %4, %5}], [%2], %7;\n}"
                 ::"r"(dst), "l"(m), "r"(bar), "r"(c0), "r"(c1), "r"(c2), "r"(bytes), "h"((unsigned short)3) : "memory");
}
__device__ __forceinline__ void bulk_s2g(void* dst, uint32_t src, uint32_t bytes) {
    asm volatile("cp.async.bulk.global.shared::cta.bulk_group [%0], [%1], %2;" ::"l"(dst), "r"(src), "r"(bytes) : "memory");
}
__device__ __forceinline__ void prefetch_map(const CUtensorMap* m) { asm volatile("prefetch.tensormap [%0];" ::"l"(m) : "memory"); }

constexpr uint32_t DESC_HI = 64u | (1u << 30);
__device__ __forceinline__ uint32_t desc_lo(uint32_t addr) { return ((addr & 0x3FFFF) >> 4) | (1u << 16); }
__device__ __forceinline__ void wg_fence() { asm volatile("wgmma.fence.sync.aligned;" ::: "memory"); }
__device__ __forceinline__ void wg_commit() { asm volatile("wgmma.commit_group.sync.aligned;" ::: "memory"); }
__device__ __forceinline__ void wg_wait0() { asm volatile("wgmma.wait_group.sync.aligned 0;" ::: "memory"); }
template <int TA>
__device__ __forceinline__ void wgmma_n32(float (&d)[16], uint32_t alo, uint32_t blo, int scale_d) {
    asm volatile("{\n.reg .pred p;\n.reg .b64 da, db;\nsetp.ne.b32 p, %18, 0;\nmov.b64 da, {%16, %20};\nmov.b64 db, {%17, %20};\n"
                 "wgmma.mma_async.sync.aligned.m64n32k16.f32.bf16.bf16 "
                 "{%0,%1,%2,%3,%4,%5,%6,%7,%8,%9,%10,%11,%12,%13,%14,%15}, da, db, p, 1, 1, %19, 0;\n}"
                 : "+f"(d[0]), "+f"(d[1]), "+f"(d[2]), "+f"(d[3]), "+f"(d[4]), "+f"(d[5]), "+f"(d[6]), "+f"(d[7]),
                   "+f"(d[8]), "+f"(d[9]), "+f"(d[10]), "+f"(d[11]), "+f"(d[12]), "+f"(d[13]), "+f"(d[14]), "+f"(d[15])
                 : "r"(alo), "r"(blo), "r"(scale_d), "n"(TA), "n"(DESC_HI));
}
template <int N>
__device__ __forceinline__ void reg_fence(float (&d)[N]) {
#pragma unroll
    for (int i = 0; i < N; i++) asm volatile("" : "+f"(d[i])::"memory");
}

#define TS(slot)
#define TS0(slot)

__device__ __forceinline__ unsigned int gtimer_lo() {
    unsigned long long t;
    asm volatile("mov.u64 %0, %globaltimer;" : "=l"(t));
    return (unsigned int)t;
}
__device__ __forceinline__ unsigned int clock32() { unsigned int c; asm volatile("mov.u32 %0, %clock;" : "=r"(c)); return c; }
__device__ __forceinline__ void spin(int cycles) {
    if (cycles <= 0) return;
    const unsigned int t0 = clock32();
#pragma unroll 1
    while (clock32() - t0 < (unsigned int)cycles) {}
}
__device__ __forceinline__ unsigned int ld_cnt(const unsigned int* p) {
    unsigned int v;
    asm volatile("ld.relaxed.gpu.global.u32 %0, [%1];" : "=r"(v) : "l"(p) : "memory");
    return v;
}
__device__ __forceinline__ void wait_cnt(const unsigned int* p, unsigned int target) {
    int it = 0;
#pragma unroll 1
    while ((int)(ld_cnt(p) - target) < 0) { if (++it > SPIN_LIMIT) break; }
}
__device__ __forceinline__ void red_cnt(unsigned int* p) { asm volatile("red.relaxed.gpu.global.add.u32 [%0], 1;" ::"l"(p) : "memory"); }

__device__ __forceinline__ uint32_t smem_base() {
    extern __shared__ __align__(1024) uint8_t smem_dyn[];
    return smem_u32(smem_dyn);
}

__device__ __forceinline__ void gemv_y_load(uint32_t (&a)[8][4]) {
    const int lane = threadIdx.x & 31, warp = threadIdx.x >> 5;
    const int blk = lane >> 3, r8 = lane & 7;
    const int ch = (warp & 3) * 2 + (blk & 1);
    const uint32_t arow = smem_base() + OFF_Y + (warp >> 2) * 16384 + ((blk >> 1) * 8 + r8) * 128 + ((ch ^ r8) << 4);
#pragma unroll
    for (int k = 0; k < 8; k++) ldsm4t(a[k], arow + k * 16 * 128);
}
__device__ __forceinline__ void gemv_y_put(const uint32_t (&a)[8][4], uint4* dst, uint32_t act, uint32_t tag) {
    const int lane = threadIdx.x & 31, warp = threadIdx.x >> 5;
    const uint32_t brow = act + (lane & 3) * 272 + (lane >> 3) * 16;
    uint32_t b[4][4];
#pragma unroll
    for (int k = 0; k < 4; k++) ldsm4(b[k], brow + k * 64);
    float d[4] = {0.f, 0.f, 0.f, 0.f}, e[4] = {0.f, 0.f, 0.f, 0.f};
#pragma unroll
    for (int k = 0; k < 4; k++) {
        mma16816(d, a[2 * k], b[k][0], b[k][1]);
        mma16816(e, a[2 * k + 1], b[k][2], b[k][3]);
    }
    const uint32_t x = (__float_as_uint(d[0] + e[0]) & ~3u) | tag;
    const float y = d[1] + e[1], z = d[2] + e[2], w = d[3] + e[3];
    if ((lane & 3) < 2) st128(dst + warp * 16 + (lane >> 2) * 2 + (lane & 3), make_uint4(x, __float_as_uint(y), __float_as_uint(z), __float_as_uint(w)));
}

__device__ __forceinline__ void gemv_512x16(float (&d)[4], uint32_t tile, uint32_t act, int k0, int nk2, int lane) {
    const int blk = lane >> 3, r8 = lane & 7;
    uint32_t arow = tile + (k0 + (blk >> 1) * 8 + r8) * 32 + (((blk & 1) ^ ((r8 >> 2) & 1)) << 4);
    uint32_t brow = act + (r8 & 3) * 1040 + (k0 + blk * 8) * 2;
#pragma unroll 2
    for (int k2 = 0; k2 < nk2; k2++) {
        uint32_t b[4], a0[4], a1[4];
        ldsm4(b, brow);
        ldsm4t(a0, arow);
        ldsm4t(a1, arow + 512);
        mma16816(d, a0, b[0], b[1]);
        mma16816(d, a1, b[2], b[3]);
        brow += 64;
        arow += 1024;
    }
}

__device__ __noinline__ float4 reduce16(const uint2* base, int n, uint32_t par, int delay) {
    const int t = threadIdx.x, lane = t & 31, warp = t >> 5;
    const uint32_t SCR = smem_base() + OFF_SCR;
    const int pp = t >> 2;
    const uint2* p0 = base + (size_t)pp * 512 + blockIdx.x * 4 + (t & 3);
    const bool act1 = pp + 64 < n;
    spin(delay);
    uint2 u, v = make_uint2(par, 0);
    int it = 0;
#pragma unroll 1
    do { u = ld64(p0); if (act1) v = ld64(p0 + 64 * 512); } while (!__all_sync(~0u, (((u.x ^ par) | (v.x ^ par)) & 1u) == 0) && ++it < SPIN_LIMIT);
    float4 a = as_f4(u);
    if (act1) add4(a, as_f4(v));
#pragma unroll
    for (int of = 4; of <= 16; of <<= 1) {
        a.x += __shfl_xor_sync(~0u, a.x, of); a.y += __shfl_xor_sync(~0u, a.y, of);
        a.z += __shfl_xor_sync(~0u, a.z, of); a.w += __shfl_xor_sync(~0u, a.w, of);
    }
    if (lane < 4) stsf4(SCR + (warp * 4 + lane) * 16, a);
    bar_main();
    float4 r = make_float4(0.f, 0.f, 0.f, 0.f);
    if (t < 4) {
#pragma unroll
        for (int w = 0; w < 8; w++) add4(r, ldsf4(SCR + (w * 4 + t) * 16));
    }
    return r;
}
__device__ __forceinline__ void sts_frag(uint32_t base, uint32_t stride, int m, int b0, float x, float y, float z, float w) {
    const uint32_t a = base + b0 * stride + m * 2;
    sts16(a, x); sts16(a + stride, y); sts16(a + 16, z); sts16(a + stride + 16, w);
}

__global__ void __cluster_dims__(2, 1, 1) __launch_bounds__(NTHREADS, 1) fused_kernel(const __grid_constant__ Params p) {
    extern __shared__ __align__(1024) uint8_t smem[];
    const uint32_t sb = smem_base();
    const int t = threadIdx.x, lane = t & 31;
    const int warp = __shfl_sync(0xffffffffu, t >> 5, 0);
    const int i = blockIdx.x;
    const int hh = i >> 2, jj = i & 3;
    const int bb = i >> 5, chunk = i & 31;
    const uint32_t rank = i & 1;
    auto BAR = [&](int k) { return sb + OFF_BAR + k * 8; };
    const uint32_t MISC = sb + OFF_MISC;

    if (warp == 8) {
        if (lane == 0) {
            TS(0);
            prefetch_map(&p.wmoda);
            prefetch_map(&p.wq);
            mbar_init(BAR(B_WA), 1);
            mbar_init(BAR(0), 1);
            asm volatile("fence.mbarrier_init.release.cluster;" ::: "memory");
            fence_async_smem();
            mbar_expect_tx(BAR(B_WA), 8192);
        }
        __syncwarp();
        uint64_t pol;
        asm volatile("createpolicy.fractional.L2::evict_first.b64 %0, 1.0;" : "=l"(pol));
        tma2d_na(sb + OFF_Z, &p.wmoda, 16 * hh, jj * 128, BAR(B_WA), pol);
        tma2d_na(sb + OFF_Z + 4096, &p.wmoda, 512 + 16 * hh, jj * 128, BAR(B_WA), pol);
        tma2d(sb + OFF_Y, &p.wq, hh * 128, jj * 128, BAR(0), 8192, pol);
        unsigned int due = gtimer_lo() + DT_0;
        if (lane == 0) {
            if (sb & 1023u) __trap();
#pragma unroll
            for (int k = 1; k < 4; k++) mbar_init(BAR(k), 1);
            asm volatile("fence.mbarrier_init.release.cluster;" ::: "memory");
            fence_async_smem();
        }
        __syncwarp();
        asm volatile("bar.arrive 4, 320;" ::: "memory");
        auto pace_dt = [&](int it, unsigned int dt) {
            if (it >= WINDOW) mbar_wait(BAR(0) + (it - WINDOW) * 8);
            int spin_it = 0;
#pragma unroll 1
            while ((int)(gtimer_lo() - due) < 0 && ++spin_it < SPIN_LIMIT) {}
            due += dt;
        };
        auto pace = [&](int it) { pace_dt(it, it < B_KV ? DT_F : (it < B_W1 ? DT_T : DT_T2)); };
        auto tile128 = [&](const CUtensorMap* m, int first, uint32_t dst, int k0) {
#pragma unroll 1
            for (int k = k0; k < 4; k++) {
                pace(first + k);
                tma2d(dst + k * 8192, m, hh * 128 + (k >> 1) * 64, jj * 128 + (k & 1) * 64, BAR(0) + (first + k) * 8, 8192, pol);
            }
        };
        tile128(&p.wq, B_WQ, sb + OFF_Y, 1);
        asm volatile("bar.sync 5, 320;" ::: "memory");
        tile128(&p.wuk, B_WUK, sb + OFF_X, 0);
        TS(61);
#pragma unroll 1
        for (int s = 0; s < 16; s++) {
            pace_dt(B_KV + s, s < 8 ? DT_F : DT_S);
            tma2d(sb + OFF_KV + s * 8192, &p.kv, (s & 7) * 64, bb * 4096 + chunk * 128 + (s >> 3) * 64, BAR(B_KV) + s * 8, 8192, pol);
        }
        const unsigned int t_poll = due + GATE_NS;
        if (lane == 0) sts32(MISC + 232, t_poll);
        TS(43);
        mbar_wait(BAR(B_YFREE));
#pragma unroll 1
        for (int k = 0; k < 2; k++) {
            pace(B_MOD + k);
            tma2d(sb + OFF_Z + k * 8192, &p.wmod, 1024 + 16 * i, k * 256, BAR(B_MOD) + k * 8, 8192, pol);
        }
        tile128(&p.wuv, B_WUV, sb + OFF_Y, 0);
        mbar_wait(BAR(B_XFREE));
#pragma unroll 1
        for (int k = 0; k < 4; k++) {
            pace(B_WO + k);
            tma3d(sb + OFF_X + k * 8192, &p.wo, 0, hh * 128 + jj * 32, k * 2, BAR(B_WO) + k * 8, 8192, pol);
        }
        {
            mbar_wait(BAR(B_EP));
            const unsigned int target = (lds32(MISC + 224) + 1u) * 32u;
            int it = 0;
#pragma unroll 1
            while ((int)(gtimer_lo() - t_poll) < 0 && ++it < SPIN_LIMIT) {}
            it = 0;
#pragma unroll 1
            while (!__all_sync(~0u, (int)(ld_cnt(&g_sync[(lane & 3) * 32 + 1]) - target) >= 0) && ++it < SPIN_LIMIT) {}
            if (lane == 0) mbar_arrive(BAR(B_G4));
            TS(13);
        }
        if (i < NFFN) {
            due = gtimer_lo();
            mbar_wait(BAR(B_ZFREE));
#pragma unroll 1
            for (int k = 0; k < 2; k++) {
                pace(B_W1 + k);
                tma2d(sb + OFF_Z + k * 8192, &p.w1, 16 * i, k * 256, BAR(B_W1) + k * 8, 8192, pol);
            }
            mbar_wait(BAR(B_KV0FREE));
#pragma unroll 1
            for (int k = 0; k < 2; k++) {
                pace(B_W2 + k);
                tma3d(sb + OFF_W2 + k * 8192, &p.w2, 0, 16 * i, k * 4, BAR(B_W2) + k * 8, 8192, pol);
            }
        }
        TS(40);
    } else if (warp == 9) {
        unsigned int ep = 0;
        if (lane == 0) {
            ep = ld_epoch(&g_sync[(i % NSYNC) * 32]);
            mbar_init(BAR(B_YFREE), 8);
            mbar_init(BAR(B_XFREE), 4);
            mbar_init(BAR(B_KV0FREE), 8);
            mbar_init(BAR(B_EP), 1);
            mbar_init(BAR(B_PEER0), 8);
            mbar_init(BAR(B_XCH), 1);
            mbar_init(BAR(B_G4), 1);
            mbar_init(BAR(B_XST), 2);
            mbar_expect_tx(BAR(B_XCH), 16384);
            mbar_expect_tx(BAR(B_XST), 128);
            asm volatile("fence.mbarrier_init.release.cluster;" ::: "memory");
        }
        __syncwarp();
        asm volatile("bar.arrive 5, 320;" ::: "memory");
        asm volatile("bar.arrive 4, 320;" ::: "memory");
        if (lane < 9) prefetch_map(&p.kv + lane);
        const uint4 z = make_uint4(0, 0, 0, 0);
        st128(&g_H[i * 32 + lane], z);
#pragma unroll
        for (int k = 0; k < 4; k++) st128(&g_Q[i * 128 + k * 32 + lane], z);
        uint32_t xr = 0;
        if (lane < 16) {
            const int V = i * 4 + (lane >> 2), e = lane & 3;
            const int m = (V >> 4) * 16 + ((V & 15) >> 1) + (e >> 1) * 8, b = (V & 1) * 2 + (e & 1);
            xr = ldnc16(p.x + b * 512 + m);
        }
        asm volatile("bar.sync 6, 288;" ::: "memory");
        __syncwarp();
        if (lane == 0) {
            sts32(MISC + 224, ep);
            sts32(MISC + 236, 0);
            mbar_arrive(BAR(B_EP));
        }
        mbar_wait(BAR(B_EP));
        ep = lds32(MISC + 224);
        const uint32_t tag = 1u + 2u * (ep & 1u);
        if (lane < 16) stsf(MISC + 32 + lane * 4, __uint_as_float(xr << 16));
        mbar_wait(BAR(B_P3));
        wait_cnt(&g_sync[(4 + (i & 3)) * 32 + 1], (ep + 1u) * 128u);
        __syncwarp();
        tma3d_mc(sb + OFF_X + rank * 16384, &p.qabs, 0, bb * 32, rank * 4, BAR(B_QABS), 32768);
        TS(41);
#pragma unroll 1
        for (int k = 0; k < 4; k++) st128(&g_C[i * 128 + k * 32 + lane], z);
        if (lane < 16) st128(&g_M[i * 16 + lane], z);
        {
            const uint32_t inv = ep & 1u;
            const uint4 zi = make_uint4(inv, 0, inv, 0);
            if (lane < 4) st128(reinterpret_cast<uint4*>(&g_X1[i * 8]) + lane, zi);
#pragma unroll 1
            for (int k = 0; k < 8; k++) {
                st128(reinterpret_cast<uint4*>(&g_O[i * 512]) + k * 32 + lane, zi);
                if (i < NFFN) st128(reinterpret_cast<uint4*>(&g_F[i * 512]) + k * 32 + lane, zi);
                spin(100);
            }
        }
        __syncwarp();
        if (lane == 0) mbar_arrive(BAR(B_CLR2));
        TS(44);
        mbar_wait_n(BAR(B_MOD), 2);
        float d[4] = {0.f, 0.f, 0.f, 0.f};
        gemv_512x16(d, sb + OFF_Z, sb + OFF_S, 0, 16, lane);
        __syncwarp();
        if (lane == 0) mbar_arrive(BAR(B_ZFREE));
        if ((lane & 3) < 2) put4(&g_M[i * 16 + (lane >> 2) * 2 + (lane & 3)], d[0], d[1], d[2], d[3], tag);
        __syncwarp();
        if (lane == 0 && i >= 32 && i < 96) red_cnt(&g_sync[4 * 32 + 2]);
        TS(42);
        {
            const float4 v = get4(&g_M[((lane >> 2) & 1) * 3 * 512 + i * 4 + (lane & 3)], lane < 8, tag);
            if (lane < 8) stsf4(MISC + 96 + lane * 16, v);
        }
        __syncwarp();
        if (lane == 0) {
            if (i < NFFN) {
                wait_cnt(&g_sync[4 * 32 + 2], (ep + 1u) * 64u);
                mbar_wait(BAR(B_KV0FREE));
                asm volatile("fence.proxy.async.global;" ::: "memory");
                mbar_expect_tx(BAR(B_MODV), 16384);
                asm volatile("cp.async.bulk.shared::cluster.global.mbarrier::complete_tx::bytes [%0], [%1], %2, [%3];"
                             ::"r"(sb + OFF_SBCB), "l"(&g_M[512]), "r"(16384), "r"(BAR(B_MODV)) : "memory");
            } else {
                mbar_arrive(BAR(B_MODV));
            }
            TS(45);
        }
    } else {
        const uint32_t ACT = sb + OFF_ACT, ACTB = sb + OFF_ACT + 1152, RED = sb + OFF_RED;
        const int g = lane >> 2, q = lane & 3;
        const int vrr = (lane & 15) >> 1, vb0 = (lane & 1) * 2;
        uint32_t cw[4];
        uint4 xv[2];
        uint32_t xh[4];
        {
            const uint4* xp = reinterpret_cast<const uint4*>(p.x + (warp & 3) * 512 + lane * 16);
            xv[0] = ldnc128_if(xp, warp < 4);
            xv[1] = ldnc128_if(xp + 1, warp < 4);
            const __nv_bfloat16* xq = p.x + vb0 * 512 + jj * 128 + warp * 16 + vrr;
            xh[0] = ldnc16(xq); xh[1] = ldnc16(xq + 512); xh[2] = ldnc16(xq + 8); xh[3] = ldnc16(xq + 520);
        }
#pragma unroll
        for (int b = 0; b < 4; b++) cw[b] = ldnc32(p.c + b * 512 + 2 * t);
        if (lane == 0) {
#pragma unroll
            for (int k = 0; k < 5; k++) {
                int idx = 4 + warp * 5 + k;
                if (idx >= B_YFREE) idx = (idx == 39) ? B_ZFREE : (idx == 40 ? B_P3 : (idx == 41 ? B_CLR2 : B_MODV));
                mbar_init(BAR(0) + idx * 8, 1);
            }
            asm volatile("fence.mbarrier_init.release.cluster;" ::: "memory");
        }
        __syncwarp();
        asm volatile("bar.arrive 5, 320;" ::: "memory");
        asm volatile("bar.arrive 6, 288;" ::: "memory");
        asm volatile("bar.sync 4, 320;" ::: "memory");

#pragma unroll
        for (int b = 0; b < 4; b++) {
            const float c0 = bf_lo(cw[b]), c1 = bf_hi(cw[b]);
            sts32(sb + OFF_S + b * 1040 + t * 4, pack_bf16(__fdividef(c0, 1.f + __expf(-c0)), __fdividef(c1, 1.f + __expf(-c1))));
        }
        if (warp < 4) {
            const uint32_t u[8] = {xv[0].x, xv[0].y, xv[0].z, xv[0].w, xv[1].x, xv[1].y, xv[1].z, xv[1].w};
            float s = 0.f, ss = 0.f;
#pragma unroll
            for (int k = 0; k < 8; k++) s += bf_lo(u[k]) + bf_hi(u[k]);
#pragma unroll
            for (int o = 16; o; o >>= 1) s += __shfl_xor_sync(~0u, s, o);
            const float mean = s * (1.f / 512.f);
#pragma unroll
            for (int k = 0; k < 8; k++) { const float d0 = bf_lo(u[k]) - mean, d1 = bf_hi(u[k]) - mean; ss += d0 * d0 + d1 * d1; }
#pragma unroll
            for (int o = 16; o; o >>= 1) ss += __shfl_xor_sync(~0u, ss, o);
            if (lane == 0) { stsf(MISC + warp * 8, mean); stsf(MISC + warp * 8 + 4, rsqrtf(ss * (1.f / 512.f) + 1e-5f)); }
        }
        bar_main();
        mbar_wait(BAR(B_EP));
        const unsigned int ep = lds32(MISC + 224);
        const uint32_t tag = 1u + 2u * (ep & 1u);
        const uint32_t par = (ep & 1u) ^ 1u;
        if (warp < 2) {
            mbar_wait(BAR(B_WA));
            TS0(26);
            float d[4] = {0.f, 0.f, 0.f, 0.f};
            gemv_512x16(d, sb + OFF_Z + warp * 4096 - jj * 4096, sb + OFF_S, jj * 128, 4, lane);
            if (q < 2) put4(&g_H[i * 32 + warp * 16 + g * 2 + q], d[0], d[1], d[2], d[3], tag);
        }
        TS0(1);
        mbar_wait_n(BAR(B_WQ), 4);
        uint32_t afr[8][4];
        gemv_y_load(afr);
        TS0(3);
        {
            const float4 a = get4sum4(&g_H[(4 * (8 * jj + warp)) * 32 + lane], 32, tag);
            const float cx = __shfl_down_sync(~0u, a.x, 16), cy = __shfl_down_sync(~0u, a.y, 16);
            const float cz = __shfl_down_sync(~0u, a.z, 16), cwv = __shfl_down_sync(~0u, a.w, 16);
            if (lane < 16) {
                const float2 s0 = ldsf2(MISC + vb0 * 8), s1 = ldsf2(MISC + vb0 * 8 + 8);
                sts_frag(ACT, 272, warp * 16 + vrr, vb0,
                         (__uint_as_float(xh[0] << 16) - s0.x) * s0.y * (1.f + cx) + a.x,
                         (__uint_as_float(xh[1] << 16) - s1.x) * s1.y * (1.f + cy) + a.y,
                         (__uint_as_float(xh[2] << 16) - s0.x) * s0.y * (1.f + cz) + a.z,
                         (__uint_as_float(xh[3] << 16) - s1.x) * s1.y * (1.f + cwv) + a.w);
            }
        }
        bar_main();
        TS0(2);
        gemv_y_put(afr, &g_Q[i * 128], ACT, tag);
        __syncwarp();
        if (lane == 0) mbar_arrive(BAR(B_YFREE));
        mbar_wait_n(BAR(B_WUK), 4);
        TS0(5);
        if (warp < 4) {
            const float4 a = get4sum4(&g_Q[hh * 4 * 128 + t], 128, tag);
            sts_frag(ACTB, 272, (t >> 4) * 16 + vrr, vb0, a.x, a.y, a.z, a.w);
        }
        bar_main();
        TS0(4);
        {
            float d[4] = {0.f, 0.f, 0.f, 0.f};
            const int blk = lane >> 3, r8 = lane & 7;
            const uint32_t arow = sb + OFF_X + (warp * 16 + (blk & 1) * 8 + r8) * 128;
            const uint32_t brow = ACTB + (r8 & 3) * 272 + blk * 16;
            uint32_t a[8][4], b[4][4];
#pragma unroll
            for (int k = 0; k < 8; k++) ldsm4(a[k], arow + (k >> 2) * 16384 + ((((k & 3) * 2 + (blk >> 1)) ^ r8) << 4));
#pragma unroll
            for (int k = 0; k < 4; k++) ldsm4(b[k], brow + k * 64);
            float e[4] = {0.f, 0.f, 0.f, 0.f};
#pragma unroll
            for (int k = 0; k < 4; k++) {
                mma16816(d, a[2 * k], b[k][0], b[k][1]);
                mma16816(e, a[2 * k + 1], b[k][2], b[k][3]);
            }
            d[0] += e[0]; d[1] += e[1]; d[2] += e[2]; d[3] += e[3];
            const float sc = 0.08838834764831845f * 1.4426950408889634f;
            if (q < 2) sts_frag(RED, 256, warp * 16 + g, 2 * q, d[0] * sc, d[1] * sc, d[2] * sc, d[3] * sc);
            fence_async_smem();
            bar_main();
            if (t == 0) {
#pragma unroll 1
                for (int b = 0; b < 4; b++) bulk_s2g(&g_qabs[(b * 32 + hh) * 512 + jj * 128], RED + b * 256, 256);
                asm volatile("cp.async.bulk.commit_group;" ::: "memory");
                asm volatile("cp.async.bulk.wait_group 0;" ::: "memory");
#pragma unroll
                for (int r = 0; r < 4; r++) red_cnt(&g_sync[(4 + r) * 32 + 1]);
                mbar_arrive(BAR(B_P3));
            }
            TS0(6);
        }
        const int wg = warp >> 2, wq = warp & 3;
        {
            const uint32_t MX = RED;
            const uint32_t LRED = RED + 512;
            const uint32_t OST = ACTB + 128, PST = ACTB;
            const uint32_t ALPHA = RED + 1536, MRUN = RED + 1664;
            const uint32_t dsc0 = desc_lo(sb);
            float o[4][16];
            float lsum[8];
#pragma unroll
            for (int k = 0; k < 8; k++) lsum[k] = 0.f;
            if (t < 32) stsf(MRUN + t * 4, -INFINITY);
            mbar_wait(BAR(B_QABS));
            TS0(7);
            float s[16];
            auto qk = [&](int c0, int c1) {
                uint32_t da = (dsc0 + (OFF_KV >> 4)) + wg * (65536 >> 4) + c0 * (8192 >> 4), db = (dsc0 + (OFF_X >> 4)) + c0 * (4096 >> 4);
#pragma unroll 1
                for (int cb = c0; cb < c1; cb++) {
                    mbar_wait(BAR(B_KV) + (wg * 8 + cb) * 8);
                    wg_fence();
#pragma unroll
                    for (int k = 0; k < 4; k++) wgmma_n32<0>(s, da + k * 2, db + k * 2, (cb | k) != 0);
                    wg_commit();
                    da += 8192 >> 4;
                    db += 4096 >> 4;
                }
            };
            if (wg == 1) qk(0, QK_EARLY);
#pragma unroll 1
            for (int tile = 0; tile < 2; tile++) {
                if (wg == tile) {
                    qk(tile == 0 ? 0 : QK_EARLY, 8);
                    wg_wait0();
                    reg_fence(s);
                    if (tile == 1) {
                        __syncwarp();
                        if (lane == 0) {
                            mbar_arrive(BAR(B_XFREE));
                            mbar_arrive(BAR(B_KV0FREE));
                            asm volatile("mbarrier.arrive.relaxed.cluster.shared::cluster.b64 _, [%0];" ::"r"(mapa(BAR(B_PEER0), rank ^ 1)) : "memory");
                        }
                    }
                    if (wq == 0) TS(8 + tile * 2);
                    float m[8];
#pragma unroll
                    for (int jb = 0; jb < 4; jb++) {
                        m[2 * jb] = fmaxf(s[4 * jb], s[4 * jb + 2]);
                        m[2 * jb + 1] = fmaxf(s[4 * jb + 1], s[4 * jb + 3]);
                    }
                    {
                        const bool u4 = lane & 16, u3 = lane & 8, u2 = lane & 4;
                        float h4[4], h2[2];
#pragma unroll
                        for (int k = 0; k < 4; k++) h4[k] = fmaxf(u4 ? m[k + 4] : m[k], __shfl_xor_sync(~0u, u4 ? m[k] : m[k + 4], 16));
#pragma unroll
                        for (int k = 0; k < 2; k++) h2[k] = fmaxf(u3 ? h4[k + 2] : h4[k], __shfl_xor_sync(~0u, u3 ? h4[k] : h4[k + 2], 8));
                        const float h1 = fmaxf(u2 ? h2[1] : h2[0], __shfl_xor_sync(~0u, u2 ? h2[0] : h2[1], 4));
                        stsf(MX + (wq * 32 + 8 * (g >> 1) + 2 * q + (g & 1)) * 4, h1);
                    }
                    if (tile == 0) asm volatile("bar.sync 2, 128;" ::: "memory"); else asm volatile("bar.sync 3, 128;" ::: "memory");
                    const float mold = ldsf(MRUN + tile * 128 + lane * 4);
                    const float mnew = fmaxf(fmaxf(fmaxf(ldsf(MX + lane * 4), ldsf(MX + 128 + lane * 4)), fmaxf(ldsf(MX + 256 + lane * 4), ldsf(MX + 384 + lane * 4))), mold);
                    uint32_t lo[4], hi[4];
#pragma unroll
                    for (int jb = 0; jb < 4; jb++) {
                        const float m0 = __shfl_sync(~0u, mnew, 8 * jb + 2 * q), m1 = __shfl_sync(~0u, mnew, 8 * jb + 2 * q + 1);
                        lo[jb] = pack_bf16(ex2(s[4 * jb] - m0), ex2(s[4 * jb + 1] - m1));
                        hi[jb] = pack_bf16(ex2(s[4 * jb + 2] - m0), ex2(s[4 * jb + 3] - m1));
                        lsum[2 * jb] = bf_lo(lo[jb]) + bf_lo(hi[jb]);
                        lsum[2 * jb + 1] = bf_hi(lo[jb]) + bf_hi(hi[jb]);
                    }
                    const uint32_t prow = sb + OFF_P + tile * 4096 + ((lane + 16 * rank) & 31) * 128;
                    stsm4t(prow + (((2 * wq) ^ (lane & 7)) << 4), lo[0], lo[1], lo[2], lo[3]);
                    stsm4t(prow + (((2 * wq + 1) ^ (lane & 7)) << 4), hi[0], hi[1], hi[2], hi[3]);
                    fence_async_smem();
                    if (wq == 0) { stsf(ALPHA + lane * 4, ex2(mold - mnew)); stsf(MRUN + (tile + 1) * 128 + lane * 4, mnew); }
                }
                bar_main();
                TS0(27 + tile);
                if (tile == 1) {
                    wg_wait0();
#pragma unroll
                    for (int mt = 0; mt < 4; mt++) reg_fence(o[mt]);
#pragma unroll
                    for (int jb = 0; jb < 4; jb++) {
                        const float2 a = ldsf2(ALPHA + ((8 * jb + 2 * q + 16 * rank) & 31) * 4);
#pragma unroll
                        for (int mt = 0; mt < 4; mt++) { o[mt][4 * jb] *= a.x; o[mt][4 * jb + 1] *= a.y; o[mt][4 * jb + 2] *= a.x; o[mt][4 * jb + 3] *= a.y; }
                    }
                }
                {
                    const uint32_t da = (dsc0 + (OFF_KV >> 4)) + tile * (65536 >> 4) + wg * (32768 >> 4), db = (dsc0 + (OFF_P >> 4)) + tile * (4096 >> 4);
                    wg_fence();
#pragma unroll
                    for (int mt = 0; mt < 4; mt++) {
#pragma unroll
                        for (int k = 0; k < 4; k++)
                            wgmma_n32<1>(o[mt], da + mt * (8192 >> 4) + k * (2048 >> 4), db + k * 2, tile | k);
                        wg_commit();
                    }
                }
                if (tile == 1) mbar_wait(BAR(B_PEER0));
                if (wg == tile) {
                    {
                        const bool u4 = lane & 16, u3 = lane & 8, u2 = lane & 4;
                        float h4[4], h2[2];
#pragma unroll
                        for (int k = 0; k < 4; k++) h4[k] = (u4 ? lsum[k + 4] : lsum[k]) + __shfl_xor_sync(~0u, u4 ? lsum[k] : lsum[k + 4], 16);
#pragma unroll
                        for (int k = 0; k < 2; k++) h2[k] = (u3 ? h4[k + 2] : h4[k]) + __shfl_xor_sync(~0u, u3 ? h4[k] : h4[k + 2], 8);
                        const float h1 = (u2 ? h2[1] : h2[0]) + __shfl_xor_sync(~0u, u2 ? h2[0] : h2[1], 4);
                        stsf(LRED + (warp * 32 + 8 * (g >> 1) + 2 * q + (g & 1)) * 4, h1);
                    }
                    if (tile == 1) {
                        asm volatile("bar.sync 3, 128;" ::: "memory");
                        if (wq == 0) {
                            float l0 = 0.f, l1 = 0.f;
#pragma unroll
                            for (int w = 0; w < 4; w++) { l0 += ldsf(LRED + (w * 32 + lane) * 4); l1 += ldsf(LRED + ((w + 4) * 32 + lane) * 4); }
                            const float l = l0 * ldsf(ALPHA + lane * 4) + l1;
                            const float mf = ldsf(MRUN + 256 + lane * 4);
                            if ((lane >> 4) == (int)rank) {
                                asm volatile("st.shared.v2.f32 [%0], {%1,%2};" ::"r"(OST + (lane & 15) * 8), "f"(mf), "f"(l) : "memory");
                            } else {
                                st_async2(mapa(PST + (lane & 15) * 8, rank ^ 1), mf, l, mapa(BAR(B_XST), rank ^ 1));
                            }
                            __syncwarp();
                            if (lane == 0) mbar_arrive(BAR(B_XST));
                        }
                    }
                }
                if (tile == 0 && wg == 0) {
                    wg_wait0();
                    __syncwarp();
                    if (lane == 0) {
                        mbar_arrive(BAR(B_KV0FREE));
                        asm volatile("mbarrier.arrive.relaxed.cluster.shared::cluster.b64 _, [%0];" ::"r"(mapa(BAR(B_PEER0), rank ^ 1)) : "memory");
                    }
                    TS0(9);
                }
            }
            {
                const uint32_t rx = mapa(sb + OFF_XCH + t * 16, rank ^ 1), rb = mapa(BAR(B_XCH), rank ^ 1);
                asm volatile("wgmma.wait_group.sync.aligned 3;" ::: "memory");
                reg_fence(o[0]);
                st_async4(rx, pack_bf16(o[0][8], o[0][9]), pack_bf16(o[0][10], o[0][11]), pack_bf16(o[0][12], o[0][13]), pack_bf16(o[0][14], o[0][15]), rb);
                asm volatile("wgmma.wait_group.sync.aligned 2;" ::: "memory");
                reg_fence(o[1]);
                st_async4(rx + 4096, pack_bf16(o[1][8], o[1][9]), pack_bf16(o[1][10], o[1][11]), pack_bf16(o[1][12], o[1][13]), pack_bf16(o[1][14], o[1][15]), rb);
                asm volatile("wgmma.wait_group.sync.aligned 1;" ::: "memory");
                reg_fence(o[2]);
                st_async4(rx + 8192, pack_bf16(o[2][8], o[2][9]), pack_bf16(o[2][10], o[2][11]), pack_bf16(o[2][12], o[2][13]), pack_bf16(o[2][14], o[2][15]), rb);
                wg_wait0();
                reg_fence(o[3]);
                st_async4(rx + 12288, pack_bf16(o[3][8], o[3][9]), pack_bf16(o[3][10], o[3][11]), pack_bf16(o[3][12], o[3][13]), pack_bf16(o[3][14], o[3][15]), rb);
            }
            TS0(11);
            mbar_wait(BAR(B_XST));
            float ca[4], cb[4];
#pragma unroll
            for (int k = 0; k < 4; k++) {
                const int n = 8 * (k >> 1) + 2 * q + (k & 1);
                const float2 so = ldsf2(OST + n * 8), sp = ldsf2(PST + n * 8);
                const float mx = fmaxf(so.x, sp.x);
                ca[k] = ex2(so.x - mx);
                cb[k] = ex2(sp.x - mx);
            }
#pragma unroll
            for (int mt = 0; mt < 4; mt++) {
                o[mt][0] *= ca[0]; o[mt][1] *= ca[1]; o[mt][2] *= ca[0]; o[mt][3] *= ca[1];
                o[mt][4] *= ca[2]; o[mt][5] *= ca[3]; o[mt][6] *= ca[2]; o[mt][7] *= ca[3];
            }
            if (warp == 0) {
                const float2 so = ldsf2(OST + (lane & 15) * 8), sp = ldsf2(PST + (lane & 15) * 8);
                const float mx = fmaxf(so.x, sp.x);
                const float l = so.y * ex2(so.x - mx) + sp.y * ex2(sp.x - mx);
                const float ln = __shfl_down_sync(~0u, l, 1), mn = __shfl_down_sync(~0u, mx, 1);
                if (lane < 16 && (lane & 1) == 0) put4(&g_stat[((rank * 4 + (lane >> 2)) * 64 + (i >> 1)) * 2 + ((lane >> 1) & 1)], mx, l, mn, ln, tag);
            }
            const uint32_t keep = (g == 0) ? 0xFFFEFFFEu : 0xFFFFFFFFu;
            const uint32_t tg = (g == 0) ? ((ep & 1u) ? 0u : 0x00010001u) : 0u;
            const int hl = lane & 15, mi2 = lane >> 4;
            mbar_wait(BAR(B_XCH));
            TS0(46);
#pragma unroll
            for (int mt = 0; mt < 4; mt++) {
                const uint4 r = lds128(sb + OFF_XCH + mt * 4096 + t * 16);
                const uint32_t lo0 = (pack_bf16(o[mt][0] + cb[0] * bf_lo(r.x), o[mt][1] + cb[1] * bf_hi(r.x)) & keep) | tg;
                const uint32_t hi0 = (pack_bf16(o[mt][2] + cb[0] * bf_lo(r.y), o[mt][3] + cb[1] * bf_hi(r.y)) & keep) | tg;
                const uint32_t lo1 = (pack_bf16(o[mt][4] + cb[2] * bf_lo(r.z), o[mt][5] + cb[3] * bf_hi(r.z)) & keep) | tg;
                const uint32_t hi1 = (pack_bf16(o[mt][6] + cb[2] * bf_lo(r.w), o[mt][7] + cb[3] * bf_hi(r.w)) & keep) | tg;
                const uint32_t row = sb + OFF_STG + (wg * 2 + (mt >> 1)) * 4096 + hl * 256;
                const int ch = (mt & 1) * 8 + wq * 2 + mi2;
                stsm4t(row + ((ch ^ (hl & 7)) << 4), lo0, lo1, hi0, hi1);
            }
            fence_async_smem();
            if (wg == 0) asm volatile("bar.sync 2, 128;" ::: "memory"); else asm volatile("bar.sync 3, 128;" ::: "memory");
            if (warp == 4) TS(47);
            if (wq == 0 && lane == 0) {
                bulk_s2g(&g_part[i * 1024 + wg * 512], sb + OFF_STG + wg * 8192, 8192);
                asm volatile("cp.async.bulk.commit_group;" ::: "memory");
                asm volatile("cp.async.bulk.wait_group 0;" ::: "memory");
                if (atomicAdd(reinterpret_cast<unsigned int*>(smem + OFF_MISC + 236), 1u) == 1u) red_cnt(&g_sync[bb * 32 + 1]);
            }
            TS0(12);
        }
        mbar_wait(BAR(B_CLR2));
        const uint32_t SCR = sb + OFF_SCR;
        {
            const int b = warp >> 1;
            const uint32_t ptag = par;
            const int pi = lane >> 3, v = (warp & 1) * 8 + (lane & 7);
            const uint4* sp = &g_stat[((hh >> 2) * 64 + b * 16 + (lane & 15)) * 2 + ((hh >> 1) & 1)];
            const uint4* src = &g_part[(2 * (b * 16 + pi) + (hh >> 4)) * 1024 + (jj * 16 + (hh & 15)) * 16 + v];
            float acc[8];
            int it = 0;
            bool ok;
            mbar_wait_n(BAR(B_WUV), 4);
            gemv_y_load(afr);
            float wi;
            {
                const unsigned int t_stat = lds32(MISC + 232) - STAT_LEAD;
#pragma unroll 1
                while ((int)(gtimer_lo() - t_stat) < 0 && ++it < SPIN_LIMIT) {}
                const float4 su = get4(sp, true, tag);
                const float mi = (hh & 1) ? su.z : su.x, li = (hh & 1) ? su.w : su.y;
                float mx = mi;
#pragma unroll
                for (int of = 8; of; of >>= 1) mx = fmaxf(mx, __shfl_xor_sync(~0u, mx, of));
                wi = ex2(mi - mx);
                float L = wi * li;
#pragma unroll
                for (int of = 8; of; of >>= 1) L += __shfl_xor_sync(~0u, L, of);
                wi = __fdividef(wi, L);
            }
            float w4[4];
#pragma unroll
            for (int k = 0; k < 4; k++) w4[k] = __shfl_sync(~0u, wi, 4 * k + pi);
            mbar_wait(BAR(B_G4));
            it = 0;
#pragma unroll 1
            do {
                uint4 r[4];
#pragma unroll
                for (int k = 0; k < 4; k++) r[k] = ld128(src + (size_t)k * 8 * 1024);
                ok = true;
#pragma unroll
                for (int k = 0; k < 8; k++) acc[k] = 0.f;
#pragma unroll
                for (int k = 0; k < 4; k++) {
                    const float w = w4[k];
                    ok = ok & ((r[k].x & 1u) == ptag);
                    acc[0] += w * bf_lo(r[k].x); acc[1] += w * bf_hi(r[k].x);
                    acc[2] += w * bf_lo(r[k].y); acc[3] += w * bf_hi(r[k].y);
                    acc[4] += w * bf_lo(r[k].z); acc[5] += w * bf_hi(r[k].z);
                    acc[6] += w * bf_lo(r[k].w); acc[7] += w * bf_hi(r[k].w);
                }
            } while (!__all_sync(~0u, ok) && ++it < SPIN_LIMIT);
            {
                const bool u4 = lane & 16, u3 = lane & 8;
                float h4[4], h2[2];
#pragma unroll
                for (int k = 0; k < 4; k++) h4[k] = (u4 ? acc[k + 4] : acc[k]) + __shfl_xor_sync(~0u, u4 ? acc[k] : acc[k + 4], 16);
#pragma unroll
                for (int k = 0; k < 2; k++) h2[k] = (u3 ? h4[k + 2] : h4[k]) + __shfl_xor_sync(~0u, u3 ? h4[k] : h4[k + 2], 8);
                const int ch = v ^ (hh & 7);
                sts32(ACT + b * 272 + (ch * 8 + (u4 ? 4 : 0) + (u3 ? 2 : 0)) * 2, pack_bf16(h2[0], h2[1]));
            }
            bar_main();
            TS0(14);
        }
        gemv_y_put(afr, &g_C[i * 128], ACT, tag);
        TS0(17);
        mbar_wait_n(BAR(B_WO), 4);
        {
            const int blk = lane >> 3, r8 = lane & 7;
            const uint32_t wb = sb + OFF_X + warp * 4096 + ((blk >> 1) * 8 + r8) * 128;
#pragma unroll
            for (int mt = 0; mt < 4; mt++) {
                const uint32_t co = ((2 * mt + (blk & 1)) ^ r8) << 4;
                ldsm4t(afr[2 * mt], wb + co);
                ldsm4t(afr[2 * mt + 1], wb + 16 * 128 + co);
            }
        }
        if (warp == 0) {
            const float4 a = get4sum4(&g_C[hh * 4 * 128 + jj * 32 + lane], 128, tag);
            sts_frag(ACTB, 80, (t >> 4) * 16 + vrr, vb0, a.x, a.y, a.z, a.w);
        }
        bar_main();
        TS0(16);
        {
            uint32_t b[4];
            ldsm4(b, ACTB + (lane & 3) * 80 + (lane >> 3) * 16);
            uint32_t px[4], py[4];
#pragma unroll
            for (int mt = 0; mt < 4; mt++) {
                float d[4] = {0.f, 0.f, 0.f, 0.f};
                mma16816(d, afr[2 * mt], b[0], b[1]);
                mma16816(d, afr[2 * mt + 1], b[2], b[3]);
                px[mt] = (pack_bf16(d[0], d[1]) & ~1u) | par;
                py[mt] = pack_bf16(d[2], d[3]);
            }
            if (q < 2) {
                uint2* dst = &g_O[i * 512 + warp * 64 + g * 2 + q];
#pragma unroll
                for (int mt = 0; mt < 4; mt++) st64(dst + mt * 16, px[mt], py[mt]);
            }
            TS0(18);
        }
        const int V = i * 4 + (t & 3);
        const int vm = (V >> 4) * 16 + ((V & 15) >> 1), vb = (V & 1) * 2;
        float4 x1 = make_float4(0.f, 0.f, 0.f, 0.f);
        {
            mbar_wait(BAR(B_MODV));
            const float4 r = reduce16(g_O, 128, par, G6ADELAY);
            if (t < 4) {
                const float4 x0 = ldsf4(MISC + 32 + t * 16), ga = ldsf4(MISC + 96 + t * 16);
                x1 = make_float4(x0.x + ga.x * r.x, x0.y + ga.y * r.y, x0.z + ga.z * r.z, x0.w + ga.w * r.w);
                put2(&g_X1[i * 8 + t], x1.x, x1.y, x1.z, x1.w, par);
            }
            TS0(19);
        }
        if (i < NFFN) {
            float4 mv[4];
#pragma unroll
            for (int k = 0; k < 4; k++) {
                uint4 u = lds128(sb + OFF_SBCB + (t + 256 * k) * 16);
                int it = 0;
                while ((u.x & 3u) != tag && ++it < SPIN_LIMIT) u = ld128(&g_M[512 + t + 256 * k]);
                mv[k] = as_f4(u);
            }
            mbar_wait_n(BAR(B_W1), 4);
            {
                const int blk = lane >> 3, r8 = lane & 7;
                const uint32_t w1r = sb + OFF_Z + (warp * 64 + (blk >> 1) * 8 + r8) * 32 + (((blk & 1) ^ ((r8 >> 2) & 1)) << 4);
                const uint32_t w2r = sb + OFF_W2 + warp * 2048 + ((blk >> 1) * 8 + r8) * 128;
#pragma unroll
                for (int k = 0; k < 4; k++) {
                    ldsm4t(afr[k], w1r + k * 512);
                    ldsm4t(afr[4 + k], w2r + (((2 * k + (blk & 1)) ^ r8) << 4));
                }
            }
            TS0(21);
            uint2 ua, ub;
            {
                int it = 0;
#pragma unroll 1
                do { ua = ld64(&g_X1[(t >> 2) * 8 + (t & 3)]); ub = ld64(&g_X1[(t >> 2) * 8 + (t & 3) + 512]); } while (!__all_sync(~0u, (((ua.x ^ par) | (ub.x ^ par)) & 1u) == 0) && ++it < SPIN_LIMIT);
            }
            const float4 a = as_f4(ua), b = as_f4(ub);
            float s0 = (a.x + a.z) + (b.x + b.z), s1 = (a.y + a.w) + (b.y + b.w);
            float q0 = (a.x * a.x + a.z * a.z) + (b.x * b.x + b.z * b.z), q1 = (a.y * a.y + a.w * a.w) + (b.y * b.y + b.w * b.w);
#pragma unroll
            for (int of = 2; of <= 16; of <<= 1) {
                s0 += __shfl_xor_sync(~0u, s0, of); s1 += __shfl_xor_sync(~0u, s1, of);
                q0 += __shfl_xor_sync(~0u, q0, of); q1 += __shfl_xor_sync(~0u, q1, of);
            }
            const uint32_t ST = SCR + 1024, ACT2 = SCR + 4096;
            if (lane < 2) stsf4(ST + (warp * 2 + lane) * 16, make_float4(s0, q0, s1, q1));
            bar_main();
            TS0(20);
            float4 tot = make_float4(0.f, 0.f, 0.f, 0.f);
#pragma unroll
            for (int w = 0; w < 8; w++) add4(tot, ldsf4(ST + (w * 2 + (t & 1)) * 16));
            const float mean0 = tot.x * (1.f / 512.f), mean1 = tot.z * (1.f / 512.f);
            const float r0 = rsqrtf(fmaxf(tot.y * (1.f / 512.f) - mean0 * mean0, 0.f) + 1e-5f);
            const float r1 = rsqrtf(fmaxf(tot.w * (1.f / 512.f) - mean1 * mean1, 0.f) + 1e-5f);
            const int m0 = (t >> 4) * 16 + vrr;
            sts_frag(ACT2, 1040, m0, vb0, (a.x - mean0) * r0 * (1.f + mv[2].x) + mv[0].x, (a.y - mean1) * r1 * (1.f + mv[2].y) + mv[0].y,
                     (a.z - mean0) * r0 * (1.f + mv[2].z) + mv[0].z, (a.w - mean1) * r1 * (1.f + mv[2].w) + mv[0].w);
            sts_frag(ACT2, 1040, m0 + 256, vb0, (b.x - mean0) * r0 * (1.f + mv[3].x) + mv[1].x, (b.y - mean1) * r1 * (1.f + mv[3].y) + mv[1].y,
                     (b.z - mean0) * r0 * (1.f + mv[3].z) + mv[1].z, (b.w - mean1) * r1 * (1.f + mv[3].w) + mv[1].w);
            bar_main();
            float d[4] = {0.f, 0.f, 0.f, 0.f};
            {
                const uint32_t brow = ACT2 + (lane & 3) * 1040 + (warp * 64 + (lane >> 3) * 8) * 2;
                uint32_t b0[4], b1[4];
                ldsm4(b0, brow);
                ldsm4(b1, brow + 64);
                float e[4] = {0.f, 0.f, 0.f, 0.f};
                mma16816(d, afr[0], b0[0], b0[1]);
                mma16816(e, afr[1], b0[2], b0[3]);
                mma16816(d, afr[2], b1[0], b1[1]);
                mma16816(e, afr[3], b1[2], b1[3]);
                d[0] += e[0]; d[1] += e[1]; d[2] += e[2]; d[3] += e[3];
            }
            const uint32_t HR = SCR + 2048;
            if (q < 2) {
                const uint32_t a0 = HR + (warp * 64 + (2 * q) * 16 + (g >> 1) * 4 + (g & 1)) * 4;
                stsf(a0, d[0]); stsf(a0 + 64, d[1]); stsf(a0 + 8, d[2]); stsf(a0 + 72, d[3]);
            }
            bar_main();
            float4 hs = ldsf4(HR + ((g & 3) * 16 + q * 4) * 4);
#pragma unroll
            for (int w = 1; w < 8; w++) add4(hs, ldsf4(HR + (w * 64 + (g & 3) * 16 + q * 4) * 4));
            const uint32_t b0r = pack_bf16(fmaxf(hs.x, 0.f), fmaxf(hs.y, 0.f)), b1r = pack_bf16(fmaxf(hs.z, 0.f), fmaxf(hs.w, 0.f));
            TS0(22);
            uint32_t px[4], py[4];
#pragma unroll
            for (int mt = 0; mt < 4; mt++) {
                float e[4] = {0.f, 0.f, 0.f, 0.f};
                mma16816(e, afr[4 + mt], b0r, b1r);
                px[mt] = (pack_bf16(e[0], e[1]) & ~1u) | par;
                py[mt] = pack_bf16(e[2], e[3]);
            }
            if (q < 2) {
                uint2* dst = &g_F[i * 512 + warp * 64 + g * 2 + q];
#pragma unroll
                for (int mt = 0; mt < 4; mt++) st64(dst + mt * 16, px[mt], py[mt]);
            }
            TS0(23);
        }
        {
            const float4 r = reduce16(g_F, NFFN, par, i < NFFN ? HOPDELAY : FFNDELAY);
            if (t < 4) {
                const float4 gb = ldsf4(MISC + 96 + 64 + t * 16);
                p.out[vb * 512 + vm] = __float2bfloat16_rn(x1.x + gb.x * r.x);
                p.out[(vb + 1) * 512 + vm] = __float2bfloat16_rn(x1.y + gb.y * r.y);
                p.out[vb * 512 + vm + 8] = __float2bfloat16_rn(x1.z + gb.z * r.z);
                p.out[(vb + 1) * 512 + vm + 8] = __float2bfloat16_rn(x1.w + gb.w * r.w);
            }
            if (i == 0 && t < NSYNC) g_sync[t * 32] = ep + 1u;
            TS0(24);
        }
    }
}

typedef CUresult (*EncodeFn)(CUtensorMap*, CUtensorMapDataType, cuuint32_t, void*, const cuuint64_t*, const cuuint64_t*, const cuuint32_t*,
                             const cuuint32_t*, CUtensorMapInterleave, CUtensorMapSwizzle, CUtensorMapL2promotion, CUtensorMapFloatOOBfill);

void make_map(EncodeFn enc, CUtensorMap* m, const void* base, int rank, const cuuint64_t* dims, const cuuint64_t* strides, const cuuint32_t* box,
              CUtensorMapSwizzle sw) {
    cuuint32_t es[3] = {1, 1, 1};
    CUresult r = enc(m, CU_TENSOR_MAP_DATA_TYPE_BFLOAT16, rank, const_cast<void*>(base), dims, strides, box, es, CU_TENSOR_MAP_INTERLEAVE_NONE, sw,
                     CU_TENSOR_MAP_L2_PROMOTION_NONE, CU_TENSOR_MAP_FLOAT_OOB_FILL_NONE);
    if (r != CUDA_SUCCESS) fprintf(stderr, "cuTensorMapEncodeTiled failed: %d\n", (int)r);
}
void map2d(EncodeFn enc, CUtensorMap* m, const void* base, uint64_t rows, uint64_t cols, uint32_t boxr, uint32_t boxc, CUtensorMapSwizzle sw) {
    cuuint64_t dims[2] = {cols, rows};
    cuuint64_t strides[1] = {cols * 2};
    cuuint32_t box[2] = {boxc, boxr};
    make_map(enc, m, base, 2, dims, strides, box, sw);
}
void map3d(EncodeFn enc, CUtensorMap* m, const void* base, uint64_t rows, uint32_t boxr, uint32_t boxb) {
    cuuint64_t dims[3] = {64, rows, 8};
    cuuint64_t strides[2] = {1024, 128};
    cuuint32_t box[3] = {64, boxr, boxb};
    make_map(enc, m, base, 3, dims, strides, box, CU_TENSOR_MAP_SWIZZLE_128B);
}

}

extern "C" void kernel_launch(void* const* d_in, const int* in_sizes, int n_in, void* d_out, int out_size) {
    (void)in_sizes; (void)n_in; (void)out_size;
    static EncodeFn enc = nullptr;
    static void* qabs_ptr = nullptr;
    static bool fits = false;
    if (!enc) {
        void* fn = nullptr;
        cudaDriverEntryPointQueryResult st;
        cudaGetDriverEntryPoint("cuTensorMapEncodeTiled", &fn, cudaEnableDefault, &st);
        enc = (EncodeFn)fn;
        cudaFuncSetAttribute(fused_kernel, cudaFuncAttributeMaxDynamicSharedMemorySize, SMEM_BYTES);
        cudaGetSymbolAddress(&qabs_ptr, g_qabs);
        cudaLaunchConfig_t cfg = {};
        cfg.gridDim = dim3(NCTA);
        cfg.blockDim = dim3(NTHREADS);
        cfg.dynamicSmemBytes = SMEM_BYTES;
        cudaLaunchAttribute at[1];
        at[0].id = cudaLaunchAttributeClusterDimension;
        at[0].val.clusterDim.x = 2; at[0].val.clusterDim.y = 1; at[0].val.clusterDim.z = 1;
        cfg.attrs = at;
        cfg.numAttrs = 1;
        int nclusters = 0;
        if (cudaOccupancyMaxActiveClusters(&nclusters, fused_kernel, &cfg) != cudaSuccess) { (void)cudaGetLastError(); nclusters = NCTA / 2; }
        fits = nclusters >= NCTA / 2;
        if (!fits) fprintf(stderr, "fused_kernel: only %d of %d clusters can be resident on this device\n", nclusters, NCTA / 2);
    }
    if (!enc || !fits) return;
    Params p;
    map2d(enc, &p.kv, d_in[1], 16384, 512, 64, 64, CU_TENSOR_MAP_SWIZZLE_128B);
    map2d(enc, &p.wq, d_in[2], 512, 4096, 64, 64, CU_TENSOR_MAP_SWIZZLE_128B);
    map2d(enc, &p.wuk, d_in[3], 512, 4096, 64, 64, CU_TENSOR_MAP_SWIZZLE_128B);
    map2d(enc, &p.wuv, d_in[4], 512, 4096, 64, 64, CU_TENSOR_MAP_SWIZZLE_128B);
    map3d(enc, &p.wo, d_in[5], 4096, 32, 2);
    map2d(enc, &p.w1, d_in[7], 512, 1376, 256, 16, CU_TENSOR_MAP_SWIZZLE_32B);
    map3d(enc, &p.w2, d_in[8], 1376, 16, 4);
    map2d(enc, &p.wmod, d_in[10], 512, 3072, 256, 16, CU_TENSOR_MAP_SWIZZLE_32B);
    map3d(enc, &p.qabs, qabs_ptr, 128, 32, 4);
    map2d(enc, &p.wmoda, d_in[10], 512, 3072, 128, 16, CU_TENSOR_MAP_SWIZZLE_32B);
    p.x = (const __nv_bfloat16*)d_in[0];
    p.c = (const __nv_bfloat16*)d_in[9];
    p.out = (__nv_bfloat16*)d_out;
    fused_kernel<<<NCTA, NTHREADS, SMEM_BYTES, cudaStreamPerThread>>>(p);
}
```

```cpp
#include <cuda_runtime.h>
#include <cuda_bf16.h>
#include <cuda.h>
#include <stdint.h>
#include <stdio.h>

namespace {

constexpr int NCTA = 128;
constexpr int NTHREADS = 320;
constexpr int NFFN = 86;
#define WINDOW 5
#define DT_0 500
#define DT_F 340
#define DT_S 325
#define DT_T 320
#define DT_T2 300
#define QK_EARLY 4
#define GATE_NS 3600
#define STAT_LEAD 200
#define G6ADELAY 450
#define HOPDELAY 300
#define FFNDELAY 2300

constexpr uint32_t OFF_KV = 0;
constexpr uint32_t OFF_X = 131072;
constexpr uint32_t OFF_Y = 163840;
constexpr uint32_t OFF_Z = 196608;
constexpr uint32_t OFF_P = 212992;
constexpr uint32_t OFF_S = 221184;
constexpr uint32_t OFF_ACT = 225344;
constexpr uint32_t OFF_RED = 227648;
constexpr uint32_t OFF_BAR = 229696;
constexpr uint32_t OFF_MISC = 230208;
constexpr uint32_t SMEM_BYTES = 230720;
constexpr uint32_t OFF_STG = OFF_KV;
constexpr uint32_t OFF_XCH = OFF_KV + 16384;
constexpr uint32_t OFF_W2 = OFF_KV + 32768;
constexpr uint32_t OFF_SBCB = OFF_KV + 49152;
constexpr uint32_t OFF_SCR = OFF_KV + 65536;

enum {
    B_WQ = 0,
    B_WUK = 4,
    B_KV = 8,
    B_MOD = 24,
    B_WUV = 26,
    B_WO = 30,
    B_W1 = 34,
    B_W2 = 36,
    B_QABS = 38,
    B_YFREE = 39,
    B_XFREE = 40,
    B_ZFREE = 41,
    B_KV0FREE = 42,
    B_P3 = 43,
    B_CLR2 = 44,
    B_MODV = 45,
    B_WA = 46,
    B_EP = 47,
    B_PEER0 = 48,
    B_G4 = 49,
    B_XST = 50,
    B_XCH = 51,
    B_COUNT = 55
};

struct alignas(64) Params {
    CUtensorMap kv, wq, wuk, wuv, wo, w1, w2, wmod, qabs, wmoda;
    const __nv_bfloat16* x;
    const __nv_bfloat16* c;
    __nv_bfloat16* out;
};

__device__ __align__(128) uint4 g_H[128 * 32];
__device__ __align__(128) uint4 g_Q[128 * 128];
__device__ __align__(128) __nv_bfloat16 g_qabs[4 * 32 * 512];
__device__ __align__(128) uint4 g_part[128 * 4 * 16 * 16];
__device__ __align__(128) uint4 g_stat[8 * 64 * 2];
__device__ __align__(128) uint4 g_C[128 * 128];
__device__ __align__(128) uint2 g_O[128 * 512];
__device__ __align__(128) uint2 g_X1[128 * 8];
__device__ __align__(128) uint2 g_F[NFFN * 512];
__device__ __align__(128) uint4 g_M[4 * 512];
constexpr int NSYNC = 8;
__device__ __align__(128) unsigned int g_sync[NSYNC * 32];

__device__ __forceinline__ uint32_t smem_u32(const void* p) { return (uint32_t)__cvta_generic_to_shared(p); }
__device__ __forceinline__ void mbar_init(uint32_t bar, int cnt) { asm volatile("mbarrier.init.shared::cta.b64 [%0], %1;" ::"r"(bar), "r"(cnt) : "memory"); }
__device__ __forceinline__ void mbar_expect_tx(uint32_t bar, uint32_t bytes) { asm volatile("mbarrier.arrive.expect_tx.shared::cta.b64 _, [%0], %1;" ::"r"(bar), "r"(bytes) : "memory"); }
__device__ __forceinline__ void mbar_arrive(uint32_t bar) { asm volatile("mbarrier.arrive.shared::cta.b64 _, [%0];" ::"r"(bar) : "memory"); }
constexpr int SPIN_LIMIT = 1 << 20;
__device__ __forceinline__ void mbar_wait(uint32_t bar) {
    asm volatile("{\n.reg .pred p;\n.reg .u32 n;\nmov.u32 n, 0;\n"
                 "LW:\nmbarrier.try_wait.parity.shared::cta.b64 p, [%0], 0;\n@p bra LD;\n"
                 "add.u32 n, n, 1;\nsetp.lt.u32 p, n, 262144;\n@p bra LW;\nLD:\n}" ::"r"(bar) : "memory");
}
__device__ __forceinline__ void mbar_wait_n(uint32_t bar, int n) {
#pragma unroll 1
    for (int k = 0; k < n; k++) mbar_wait(bar + k * 8);
}
__device__ __forceinline__ void bar_main() { asm volatile("bar.sync 1, 256;" ::: "memory"); }
__device__ __forceinline__ void fence_async_smem() { asm volatile("fence.proxy.async.shared::cta;" ::: "memory"); }

__device__ __forceinline__ uint4 ld128(const uint4* p) {
    uint4 v;
    asm volatile("{\n.reg .b128 t;\n.reg .b64 lo, hi;\nld.relaxed.gpu.global.b128 t, [%4];\nmov.b128 {lo, hi}, t;\nmov.b64 {%0,%1}, lo;\nmov.b64 {%2,%3}, hi;\n}"
                 : "=r"(v.x), "=r"(v.y), "=r"(v.z), "=r"(v.w) : "l"(p) : "memory");
    return v;
}
__device__ __forceinline__ void st128(uint4* p, uint4 v) {
    asm volatile("{\n.reg .b128 t;\n.reg .b64 lo, hi;\nmov.b64 lo, {%1,%2};\nmov.b64 hi, {%3,%4};\nmov.b128 t, {lo, hi};\nst.relaxed.gpu.global.b128 [%0], t;\n}"
                 ::"l"(p), "r"(v.x), "r"(v.y), "r"(v.z), "r"(v.w) : "memory");
}
__device__ __forceinline__ uint4 ldnc128_if(const void* p, bool c) {
    uint4 v;
    asm volatile("{\n.reg .pred p;\nsetp.ne.u32 p, %5, 0;\nmov.u32 %0, 0;\nmov.u32 %1, 0;\nmov.u32 %2, 0;\nmov.u32 %3, 0;\n@p ld.global.nc.v4.u32 {%0,%1,%2,%3}, [%4];\n}"
                 : "=r"(v.x), "=r"(v.y), "=r"(v.z), "=r"(v.w) : "l"(p), "r"((uint32_t)c));
    return v;
}
__device__ __forceinline__ uint32_t ldnc32(const void* p) { uint32_t v; asm volatile("ld.global.nc.u32 %0, [%1];" : "=r"(v) : "l"(p)); return v; }
__device__ __forceinline__ uint32_t ldnc16(const void* p) { uint32_t v; asm volatile("ld.global.nc.u16 %0, [%1];" : "=r"(v) : "l"(p)); return v; }
__device__ __forceinline__ unsigned int ld_epoch(const unsigned int* p) { unsigned int v; asm volatile("ld.relaxed.gpu.global.u32 %0, [%1];" : "=r"(v) : "l"(p)); return v; }
__device__ __forceinline__ void put4(uint4* p, float a, float b, float c, float d, uint32_t tag) {
    st128(p, make_uint4((__float_as_uint(a) & ~3u) | tag, __float_as_uint(b), __float_as_uint(c), __float_as_uint(d)));
}
__device__ __forceinline__ float4 as_f4(uint4 v) {
    return make_float4(__uint_as_float(v.x & ~3u), __uint_as_float(v.y), __uint_as_float(v.z), __uint_as_float(v.w));
}
__device__ __forceinline__ void add4(float4& a, const float4& b) { a.x += b.x; a.y += b.y; a.z += b.z; a.w += b.w; }
__device__ __forceinline__ float4 get4(const uint4* p, bool act, uint32_t tag) {
    uint4 v = make_uint4(tag, 0, 0, 0);
    int it = 0;
#pragma unroll 1
    do { if (act) v = ld128(p); } while (!__all_sync(~0u, (v.x & 3u) == tag) && ++it < SPIN_LIMIT);
    return as_f4(v);
}
__device__ __forceinline__ uint2 ld64(const uint2* p) { uint2 v; asm volatile("{\n.reg .b64 t;\nld.relaxed.gpu.global.b64 t, [%2];\nmov.b64 {%0,%1}, t;\n}" : "=r"(v.x), "=r"(v.y) : "l"(p) : "memory"); return v; }
__device__ __forceinline__ void st64(uint2* p, uint32_t x, uint32_t y) { asm volatile("{\n.reg .b64 t;\nmov.b64 t, {%1,%2};\nst.relaxed.gpu.global.b64 [%0], t;\n}" ::"l"(p), "r"(x), "r"(y) : "memory"); }
__device__ __forceinline__ uint32_t pack_bf16(float lo, float hi);
__device__ __forceinline__ void put2(uint2* p, float a, float b, float c, float d, uint32_t par) { st64(p, (pack_bf16(a, b) & ~1u) | par, pack_bf16(c, d)); }
__device__ __forceinline__ float4 as_f4(uint2 v) {
    return make_float4(__uint_as_float(v.x << 16), __uint_as_float(v.x & 0xffff0000u), __uint_as_float(v.y << 16), __uint_as_float(v.y & 0xffff0000u));
}
__device__ __forceinline__ float4 get4sum4(const uint4* p0, int stride, uint32_t tag) {
    uint4 u0, u1, u2, u3;
    int it = 0;
#pragma unroll 1
    do { u0 = ld128(p0); u1 = ld128(p0 + stride); u2 = ld128(p0 + 2 * stride); u3 = ld128(p0 + 3 * stride); }
    while (!__all_sync(~0u, ((u0.x ^ tag) & 3u) == 0 && ((u1.x ^ tag) & 3u) == 0 && ((u2.x ^ tag) & 3u) == 0 && ((u3.x ^ tag) & 3u) == 0) && ++it < SPIN_LIMIT);
    float4 a = as_f4(u0), b = as_f4(u2);
    add4(a, as_f4(u1));
    add4(b, as_f4(u3));
    add4(a, b);
    return a;
}
__device__ __forceinline__ uint32_t pack_bf16(float lo, float hi) {
    uint32_t r;
    asm("cvt.rn.bf16x2.f32 %0, %1, %2;" : "=r"(r) : "f"(hi), "f"(lo));
    return r;
}
__device__ __forceinline__ float bf_lo(uint32_t u) { return __uint_as_float(u << 16); }
__device__ __forceinline__ float bf_hi(uint32_t u) { return __uint_as_float(u & 0xffff0000u); }
__device__ __forceinline__ float ex2(float x) { float y; asm("ex2.approx.ftz.f32 %0, %1;" : "=f"(y) : "f"(x)); return y; }

__device__ __forceinline__ void ldsm4(uint32_t (&r)[4], uint32_t addr) {
    asm volatile("ldmatrix.sync.aligned.m8n8.x4.shared.b16 {%0,%1,%2,%3}, [%4];" : "=r"(r[0]), "=r"(r[1]), "=r"(r[2]), "=r"(r[3]) : "r"(addr) : "memory");
}
__device__ __forceinline__ void ldsm4t(uint32_t (&r)[4], uint32_t addr) {
    asm volatile("ldmatrix.sync.aligned.m8n8.x4.trans.shared.b16 {%0,%1,%2,%3}, [%4];" : "=r"(r[0]), "=r"(r[1]), "=r"(r[2]), "=r"(r[3]) : "r"(addr) : "memory");
}
__device__ __forceinline__ void stsm4t(uint32_t addr, uint32_t r0, uint32_t r1, uint32_t r2, uint32_t r3) {
    asm volatile("stmatrix.sync.aligned.m8n8.x4.trans.shared.b16 [%0], {%1,%2,%3,%4};" ::"r"(addr), "r"(r0), "r"(r1), "r"(r2), "r"(r3) : "memory");
}
__device__ __forceinline__ void mma16816(float (&d)[4], const uint32_t (&a)[4], uint32_t b0, uint32_t b1) {
    asm volatile("mma.sync.aligned.m16n8k16.row.col.f32.bf16.bf16.f32 {%0,%1,%2,%3}, {%4,%5,%6,%7}, {%8,%9}, {%0,%1,%2,%3};"
                 : "+f"(d[0]), "+f"(d[1]), "+f"(d[2]), "+f"(d[3]) : "r"(a[0]), "r"(a[1]), "r"(a[2]), "r"(a[3]), "r"(b0), "r"(b1));
}
__device__ __forceinline__ void sts32(uint32_t a, uint32_t v) { asm volatile("st.shared.b32 [%0], %1;" ::"r"(a), "r"(v) : "memory"); }
__device__ __forceinline__ void sts16(uint32_t a, float v) {
    __nv_bfloat16 h = __float2bfloat16_rn(v);
    asm volatile("st.shared.b16 [%0], %1;" ::"r"(a), "h"(*reinterpret_cast<unsigned short*>(&h)) : "memory");
}
__device__ __forceinline__ void stsf(uint32_t a, float v) { asm volatile("st.shared.f32 [%0], %1;" ::"r"(a), "f"(v) : "memory"); }
__device__ __forceinline__ void stsf4(uint32_t a, float4 v) { asm volatile("st.shared.v4.f32 [%0], {%1,%2,%3,%4};" ::"r"(a), "f"(v.x), "f"(v.y), "f"(v.z), "f"(v.w) : "memory"); }
__device__ __forceinline__ uint32_t lds32(uint32_t a) { uint32_t v; asm volatile("ld.shared.b32 %0, [%1];" : "=r"(v) : "r"(a) : "memory"); return v; }
__device__ __forceinline__ float ldsf(uint32_t a) { float v; asm volatile("ld.shared.f32 %0, [%1];" : "=f"(v) : "r"(a) : "memory"); return v; }
__device__ __forceinline__ float2 ldsf2(uint32_t a) { float2 v; asm volatile("ld.shared.v2.f32 {%0,%1}, [%2];" : "=f"(v.x), "=f"(v.y) : "r"(a) : "memory"); return v; }
__device__ __forceinline__ float4 ldsf4(uint32_t a) { float4 v; asm volatile("ld.shared.v4.f32 {%0,%1,%2,%3}, [%4];" : "=f"(v.x), "=f"(v.y), "=f"(v.z), "=f"(v.w) : "r"(a) : "memory"); return v; }
__device__ __forceinline__ uint4 lds128(uint32_t a) { uint4 v; asm volatile("ld.shared.v4.b32 {%0,%1,%2,%3}, [%4];" : "=r"(v.x), "=r"(v.y), "=r"(v.z), "=r"(v.w) : "r"(a) : "memory"); return v; }

__device__ __forceinline__ void tma2d(uint32_t dst, const CUtensorMap* m, int c0, int c1, uint32_t bar, uint32_t bytes, uint64_t pol) {
    asm volatile("{\n.reg .pred p;\nelect.sync _|p, 0xffffffff;\n"
                 "@p mbarrier.arrive.expect_tx.shared::cta.b64 _, [%2], %6;\n"
                 "@p cp.async.bulk.tensor.2d.shared::cluster.global.mbarrier::complete_tx::bytes.L2::cache_hint [%0], [%1, {%3, %4}], [%2], %5;\n}"
                 ::"r"(dst), "l"(m), "r"(bar), "r"(c0), "r"(c1), "l"(pol), "r"(bytes) : "memory");
}
__device__ __forceinline__ void tma3d(uint32_t dst, const CUtensorMap* m, int c0, int c1, int c2, uint32_t bar, uint32_t bytes, uint64_t pol) {
    asm volatile("{\n.reg .pred p;\nelect.sync _|p, 0xffffffff;\n"
                 "@p mbarrier.arrive.expect_tx.shared::cta.b64 _, [%2], %7;\n"
                 "@p cp.async.bulk.tensor.3d.shared::cluster.global.mbarrier::complete_tx::bytes.L2::cache_hint [%0], [%1, {%3, %4, %5}], [%2], %6;\n}"
                 ::"r"(dst), "l"(m), "r"(bar), "r"(c0), "r"(c1), "r"(c2), "l"(pol), "r"(bytes) : "memory");
}
__device__ __forceinline__ void tma2d_na(uint32_t dst, const CUtensorMap* m, int c0, int c1, uint32_t bar, uint64_t pol) {
    asm volatile("{\n.reg .pred p;\nelect.sync _|p, 0xffffffff;\n"
                 "@p cp.async.bulk.tensor.2d.shared::cluster.global.mbarrier::complete_tx::bytes.L2::cache_hint [%0], [%1, {%3, %4}], [%2], %5;\n}"
                 ::"r"(dst), "l"(m), "r"(bar), "r"(c0), "r"(c1), "l"(pol) : "memory");
}
__device__ __forceinline__ uint32_t mapa(uint32_t addr, uint32_t rank) {
    uint32_t r;
    asm("mapa.shared::cluster.u32 %0, %1, %2;" : "=r"(r) : "r"(addr), "r"(rank));
    return r;
}
__device__ __forceinline__ void st_async4(uint32_t raddr, uint32_t a, uint32_t b, uint32_t c, uint32_t d, uint32_t rbar) {
    asm volatile("st.async.weak.shared::cluster.mbarrier::complete_tx::bytes.v4.b32 [%0], {%1,%2,%3,%4}, [%5];" ::"r"(raddr), "r"(a), "r"(b), "r"(c), "r"(d), "r"(rbar) : "memory");
}
__device__ __forceinline__ void st_async2(uint32_t raddr, float a, float b, uint32_t rbar) {
    asm volatile("st.async.weak.shared::cluster.mbarrier::complete_tx::bytes.v2.f32 [%0], {%1,%2}, [%3];" ::"r"(raddr), "f"(a), "f"(b), "r"(rbar) : "memory");
}
__device__ __forceinline__ void tma3d_mc(uint32_t dst, const CUtensorMap* m, int c0, int c1, int c2, uint32_t bar, uint32_t bytes) {
    asm volatile("{\n.reg .pred p;\nelect.sync _|p, 0xffffffff;\n"
                 "@p mbarrier.arrive.expect_tx.shared::cta.b64 _, [%2], %6;\n"
                 "@p cp.async.bulk.tensor.3d.shared::cluster.global.mbarrier::complete_tx::bytes.multicast::cluster [%0], [%1, {%3, %4, %5}], [%2], %7;\n}"
                 ::"r"(dst), "l"(m), "r"(bar), "r"(c0), "r"(c1), "r"(c2), "r"(bytes), "h"((unsigned short)3) : "memory");
}
__device__ __forceinline__ void bulk_s2g(void* dst, uint32_t src, uint32_t bytes) {
    asm volatile("cp.async.bulk.global.shared::cta.bulk_group [%0], [%1], %2;" ::"l"(dst), "r"(src), "r"(bytes) : "memory");
}
__device__ __forceinline__ void prefetch_map(const CUtensorMap* m) { asm volatile("prefetch.tensormap [%0];" ::"l"(m) : "memory"); }

constexpr uint32_t DESC_HI = 64u | (1u << 30);
__device__ __forceinline__ uint32_t desc_lo(uint32_t addr) { return ((addr & 0x3FFFF) >> 4) | (1u << 16); }
__device__ __forceinline__ void wg_fence() { asm volatile("wgmma.fence.sync.aligned;" ::: "memory"); }
__device__ __forceinline__ void wg_commit() { asm volatile("wgmma.commit_group.sync.aligned;" ::: "memory"); }
__device__ __forceinline__ void wg_wait0() { asm volatile("wgmma.wait_group.sync.aligned 0;" ::: "memory"); }
template <int TA>
__device__ __forceinline__ void wgmma_n32(float (&d)[16], uint32_t alo, uint32_t blo, int scale_d) {
    asm volatile("{\n.reg .pred p;\n.reg .b64 da, db;\nsetp.ne.b32 p, %18, 0;\nmov.b64 da, {%16, %20};\nmov.b64 db, {%17, %20};\n"
                 "wgmma.mma_async.sync.aligned.m64n32k16.f32.bf16.bf16 "
                 "{%0,%1,%2,%3,%4,%5,%6,%7,%8,%9,%10,%11,%12,%13,%14,%15}, da, db, p, 1, 1, %19, 0;\n}"
                 : "+f"(d[0]), "+f"(d[1]), "+f"(d[2]), "+f"(d[3]), "+f"(d[4]), "+f"(d[5]), "+f"(d[6]), "+f"(d[7]),
                   "+f"(d[8]), "+f"(d[9]), "+f"(d[10]), "+f"(d[11]), "+f"(d[12]), "+f"(d[13]), "+f"(d[14]), "+f"(d[15])
                 : "r"(alo), "r"(blo), "r"(scale_d), "n"(TA), "n"(DESC_HI));
}
template <int N>
__device__ __forceinline__ void reg_fence(float (&d)[N]) {
#pragma unroll
    for (int i = 0; i < N; i++) asm volatile("" : "+f"(d[i])::"memory");
}

#define TS(slot)
#define TS0(slot)

__device__ __forceinline__ unsigned int gtimer_lo() {
    unsigned long long t;
    asm volatile("mov.u64 %0, %globaltimer;" : "=l"(t));
    return (unsigned int)t;
}
__device__ __forceinline__ unsigned int clock32() { unsigned int c; asm volatile("mov.u32 %0, %clock;" : "=r"(c)); return c; }
__device__ __forceinline__ void spin(int cycles) {
    if (cycles <= 0) return;
    const unsigned int t0 = clock32();
#pragma unroll 1
    while (clock32() - t0 < (unsigned int)cycles) {}
}
__device__ __forceinline__ unsigned int ld_cnt(const unsigned int* p) {
    unsigned int v;
    asm volatile("ld.relaxed.gpu.global.u32 %0, [%1];" : "=r"(v) : "l"(p) : "memory");
    return v;
}
__device__ __forceinline__ void wait_cnt(const unsigned int* p, unsigned int target) {
    int it = 0;
#pragma unroll 1
    while ((int)(ld_cnt(p) - target) < 0) { if (++it > SPIN_LIMIT) break; }
}
__device__ __forceinline__ void red_cnt(unsigned int* p) { asm volatile("red.relaxed.gpu.global.add.u32 [%0], 1;" ::"l"(p) : "memory"); }

__device__ __forceinline__ uint32_t smem_base() {
    extern __shared__ __align__(1024) uint8_t smem_dyn[];
    return smem_u32(smem_dyn);
}

__device__ __forceinline__ void gemv_y_load(uint32_t (&a)[8][4]) {
    const int lane = threadIdx.x & 31, warp = threadIdx.x >> 5;
    const int blk = lane >> 3, r8 = lane & 7;
    const int ch = (warp & 3) * 2 + (blk & 1);
    const uint32_t arow = smem_base() + OFF_Y + (warp >> 2) * 16384 + ((blk >> 1) * 8 + r8) * 128 + ((ch ^ r8) << 4);
#pragma unroll
    for (int k = 0; k < 8; k++) ldsm4t(a[k], arow + k * 16 * 128);
}
__device__ __forceinline__ void gemv_y_put(const uint32_t (&a)[8][4], uint4* dst, uint32_t act, uint32_t tag) {
    const int lane = threadIdx.x & 31, warp = threadIdx.x >> 5;
    const uint32_t brow = act + (lane & 3) * 272 + (lane >> 3) * 16;
    uint32_t b[4][4];
#pragma unroll
    for (int k = 0; k < 4; k++) ldsm4(b[k], brow + k * 64);
    float d[4] = {0.f, 0.f, 0.f, 0.f}, e[4] = {0.f, 0.f, 0.f, 0.f};
#pragma unroll
    for (int k = 0; k < 4; k++) {
        mma16816(d, a[2 * k], b[k][0], b[k][1]);
        mma16816(e, a[2 * k + 1], b[k][2], b[k][3]);
    }
    const uint32_t x = (__float_as_uint(d[0] + e[0]) & ~3u) | tag;
    const float y = d[1] + e[1], z = d[2] + e[2], w = d[3] + e[3];
    if ((lane & 3) < 2) st128(dst + warp * 16 + (lane >> 2) * 2 + (lane & 3), make_uint4(x, __float_as_uint(y), __float_as_uint(z), __float_as_uint(w)));
}

__device__ __forceinline__ void gemv_512x16(float (&d)[4], uint32_t tile, uint32_t act, int k0, int nk2, int lane) {
    const int blk = lane >> 3, r8 = lane & 7;
    uint32_t arow = tile + (k0 + (blk >> 1) * 8 + r8) * 32 + (((blk & 1) ^ ((r8 >> 2) & 1)) << 4);
    uint32_t brow = act + (r8 & 3) * 1040 + (k0 + blk * 8) * 2;
#pragma unroll 2
    for (int k2 = 0; k2 < nk2; k2++) {
        uint32_t b[4], a0[4], a1[4];
        ldsm4(b, brow);
        ldsm4t(a0, arow);
        ldsm4t(a1, arow + 512);
        mma16816(d, a0, b[0], b[1]);
        mma16816(d, a1, b[2], b[3]);
        brow += 64;
        arow += 1024;
    }
}

__device__ __noinline__ float4 reduce16(const uint2* base, int n, uint32_t par, int delay) {
    const int t = threadIdx.x, lane = t & 31, warp = t >> 5;
    const uint32_t SCR = smem_base() + OFF_SCR;
    const int pp = t >> 2;
    const uint2* p0 = base + (size_t)pp * 512 + blockIdx.x * 4 + (t & 3);
    const bool act1 = pp + 64 < n;
    spin(delay);
    uint2 u, v = make_uint2(par, 0);
    int it = 0;
#pragma unroll 1
    do { u = ld64(p0); if (act1) v = ld64(p0 + 64 * 512); } while (!__all_sync(~0u, (((u.x ^ par) | (v.x ^ par)) & 1u) == 0) && ++it < SPIN_LIMIT);
    float4 a = as_f4(u);
    if (act1) add4(a, as_f4(v));
#pragma unroll
    for (int of = 4; of <= 16; of <<= 1) {
        a.x += __shfl_xor_sync(~0u, a.x, of); a.y += __shfl_xor_sync(~0u, a.y, of);
        a.z += __shfl_xor_sync(~0u, a.z, of); a.w += __shfl_xor_sync(~0u, a.w, of);
    }
    if (lane < 4) stsf4(SCR + (warp * 4 + lane) * 16, a);
    bar_main();
    float4 r = make_float4(0.f, 0.f, 0.f, 0.f);
    if (t < 4) {
#pragma unroll
        for (int w = 0; w < 8; w++) add4(r, ldsf4(SCR + (w * 4 + t) * 16));
    }
    return r;
}
__device__ __forceinline__ void sts_frag(uint32_t base, uint32_t stride, int m, int b0, float x, float y, float z, float w) {
    const uint32_t a = base + b0 * stride + m * 2;
    sts16(a, x); sts16(a + stride, y); sts16(a + 16, z); sts16(a + stride + 16, w);
}

__global__ void __cluster_dims__(2, 1, 1) __launch_bounds__(NTHREADS, 1) fused_kernel(const __grid_constant__ Params p) {
    extern __shared__ __align__(1024) uint8_t smem[];
    const uint32_t sb = smem_base();
    const int t = threadIdx.x, lane = t & 31;
    const int warp = __shfl_sync(0xffffffffu, t >> 5, 0);
    const int i = blockIdx.x;
    const int hh = i >> 2, jj = i & 3;
    const int bb = i >> 5, chunk = i & 31;
    const uint32_t rank = i & 1;
    auto BAR = [&](int k) { return sb + OFF_BAR + k * 8; };
    const uint32_t MISC = sb + OFF_MISC;

    if (warp == 8) {
        if (lane == 0) {
            TS(0);
            prefetch_map(&p.wmoda);
            prefetch_map(&p.wq);
            mbar_init(BAR(B_WA), 1);
            mbar_init(BAR(0), 1);
            asm volatile("fence.mbarrier_init.release.cluster;" ::: "memory");
            fence_async_smem();
            mbar_expect_tx(BAR(B_WA), 8192);
        }
        __syncwarp();
        uint64_t pol;
        asm volatile("createpolicy.fractional.L2::evict_first.b64 %0, 1.0;" : "=l"(pol));
        tma2d_na(sb + OFF_Z, &p.wmoda, 16 * hh, jj * 128, BAR(B_WA), pol);
        tma2d_na(sb + OFF_Z + 4096, &p.wmoda, 512 + 16 * hh, jj * 128, BAR(B_WA), pol);
        tma2d(sb + OFF_Y, &p.wq, hh * 128, jj * 128, BAR(0), 8192, pol);
        unsigned int due = gtimer_lo() + DT_0;
        if (lane == 0) {
            if (sb & 1023u) __trap();
#pragma unroll
            for (int k = 1; k < 4; k++) mbar_init(BAR(k), 1);
            asm volatile("fence.mbarrier_init.release.cluster;" ::: "memory");
            fence_async_smem();
        }
        __syncwarp();
        asm volatile("bar.arrive 4, 320;" ::: "memory");
        auto pace_dt = [&](int it, unsigned int dt) {
            if (it >= WINDOW) mbar_wait(BAR(0) + (it - WINDOW) * 8);
            int spin_it = 0;
#pragma unroll 1
            while ((int)(gtimer_lo() - due) < 0 && ++spin_it < SPIN_LIMIT) {}
            due += dt;
        };
        auto pace = [&](int it) { pace_dt(it, it < B_KV ? DT_F : (it < B_W1 ? DT_T : DT_T2)); };
        auto tile128 = [&](const CUtensorMap* m, int first, uint32_t dst, int k0) {
#pragma unroll 1
            for (int k = k0; k < 4; k++) {
                pace(first + k);
                tma2d(dst + k * 8192, m, hh * 128 + (k >> 1) * 64, jj * 128 + (k & 1) * 64, BAR(0) + (first + k) * 8, 8192, pol);
            }
        };
        tile128(&p.wq, B_WQ, sb + OFF_Y, 1);
        asm volatile("bar.sync 5, 320;" ::: "memory");
        tile128(&p.wuk, B_WUK, sb + OFF_X, 0);
        TS(61);
#pragma unroll 1
        for (int s = 0; s < 16; s++) {
            pace_dt(B_KV + s, s < 8 ? DT_F : DT_S);
            tma2d(sb + OFF_KV + s * 8192, &p.kv, (s & 7) * 64, bb * 4096 + chunk * 128 + (s >> 3) * 64, BAR(B_KV) + s * 8, 8192, pol);
        }
        const unsigned int t_poll = due + GATE_NS;
        if (lane == 0) sts32(MISC + 232, t_poll);
        TS(43);
        mbar_wait(BAR(B_YFREE));
#pragma unroll 1
        for (int k = 0; k < 2; k++) {
            pace(B_MOD + k);
            tma2d(sb + OFF_Z + k * 8192, &p.wmod, 1024 + 16 * i, k * 256, BAR(B_MOD) + k * 8, 8192, pol);
        }
        tile128(&p.wuv, B_WUV, sb + OFF_Y, 0);
        mbar_wait(BAR(B_XFREE));
#pragma unroll 1
        for (int k = 0; k < 4; k++) {
            pace(B_WO + k);
            tma3d(sb + OFF_X + k * 8192, &p.wo, 0, hh * 128 + jj * 32, k * 2, BAR(B_WO) + k * 8, 8192, pol);
        }
        {
            mbar_wait(BAR(B_EP));
            const unsigned int target = (lds32(MISC + 224) + 1u) * 32u;
            int it = 0;
#pragma unroll 1
            while ((int)(gtimer_lo() - t_poll) < 0 && ++it < SPIN_LIMIT) {}
            it = 0;
#pragma unroll 1
            while (!__all_sync(~0u, (int)(ld_cnt(&g_sync[(lane & 3) * 32 + 1]) - target) >= 0) && ++it < SPIN_LIMIT) {}
            if (lane == 0) mbar_arrive(BAR(B_G4));
            TS(13);
        }
        if (i < NFFN) {
            due = gtimer_lo();
            mbar_wait(BAR(B_ZFREE));
#pragma unroll 1
            for (int k = 0; k < 2; k++) {
                pace(B_W1 + k);
                tma2d(sb + OFF_Z + k * 8192, &p.w1, 16 * i, k * 256, BAR(B_W1) + k * 8, 8192, pol);
            }
            mbar_wait(BAR(B_KV0FREE));
#pragma unroll 1
            for (int k = 0; k < 2; k++) {
                pace(B_W2 + k);
                tma3d(sb + OFF_W2 + k * 8192, &p.w2, 0, 16 * i, k * 4, BAR(B_W2) + k * 8, 8192, pol);
            }
        }
        TS(40);
    } else if (warp == 9) {
        unsigned int ep = 0;
        if (lane == 0) {
            ep = ld_epoch(&g_sync[(i % NSYNC) * 32]);
            mbar_init(BAR(B_YFREE), 8);
            mbar_init(BAR(B_XFREE), 4);
            mbar_init(BAR(B_KV0FREE), 8);
            mbar_init(BAR(B_EP), 1);
            mbar_init(BAR(B_PEER0), 8);
            mbar_init(BAR(B_G4), 1);
            mbar_init(BAR(B_XST), 2);
#pragma unroll
            for (int k = 0; k < 4; k++) { mbar_init(BAR(B_XCH + k), 1); mbar_expect_tx(BAR(B_XCH + k), 4096); }
            mbar_expect_tx(BAR(B_XST), 128);
            asm volatile("fence.mbarrier_init.release.cluster;" ::: "memory");
        }
        __syncwarp();
        asm volatile("bar.arrive 5, 320;" ::: "memory");
        asm volatile("bar.arrive 4, 320;" ::: "memory");
        if (lane < 9) prefetch_map(&p.kv + lane);
        const uint4 z = make_uint4(0, 0, 0, 0);
        st128(&g_H[i * 32 + lane], z);
#pragma unroll
        for (int k = 0; k < 4; k++) st128(&g_Q[i * 128 + k * 32 + lane], z);
        uint32_t xr = 0;
        if (lane < 16) {
            const int V = i * 4 + (lane >> 2), e = lane & 3;
            const int m = (V >> 4) * 16 + ((V & 15) >> 1) + (e >> 1) * 8, b = (V & 1) * 2 + (e & 1);
            xr = ldnc16(p.x + b * 512 + m);
        }
        asm volatile("bar.sync 6, 288;" ::: "memory");
        __syncwarp();
        if (lane == 0) {
            sts32(MISC + 224, ep);
            sts32(MISC + 236, 0);
            mbar_arrive(BAR(B_EP));
        }
        mbar_wait(BAR(B_EP));
        ep = lds32(MISC + 224);
        const uint32_t tag = 1u + 2u * (ep & 1u);
        if (lane < 16) stsf(MISC + 32 + lane * 4, __uint_as_float(xr << 16));
        mbar_wait(BAR(B_P3));
        wait_cnt(&g_sync[(4 + (i & 3)) * 32 + 1], (ep + 1u) * 128u);
        __syncwarp();
        tma3d_mc(sb + OFF_X + rank * 16384, &p.qabs, 0, bb * 32, rank * 4, BAR(B_QABS), 32768);
        TS(41);
#pragma unroll 1
        for (int k = 0; k < 4; k++) st128(&g_C[i * 128 + k * 32 + lane], z);
        if (lane < 16) st128(&g_M[i * 16 + lane], z);
        {
            const uint32_t inv = ep & 1u;
            const uint4 zi = make_uint4(inv, 0, inv, 0);
            if (lane < 4) st128(reinterpret_cast<uint4*>(&g_X1[i * 8]) + lane, zi);
#pragma unroll 1
            for (int k = 0; k < 8; k++) {
                st128(reinterpret_cast<uint4*>(&g_O[i * 512]) + k * 32 + lane, zi);
                if (i < NFFN) st128(reinterpret_cast<uint4*>(&g_F[i * 512]) + k * 32 + lane, zi);
                spin(100);
            }
        }
        __syncwarp();
        if (lane == 0) mbar_arrive(BAR(B_CLR2));
        TS(44);
        mbar_wait_n(BAR(B_MOD), 2);
        float d[4] = {0.f, 0.f, 0.f, 0.f};
        gemv_512x16(d, sb + OFF_Z, sb + OFF_S, 0, 16, lane);
        __syncwarp();
        if (lane == 0) mbar_arrive(BAR(B_ZFREE));
        if ((lane & 3) < 2) put4(&g_M[i * 16 + (lane >> 2) * 2 + (lane & 3)], d[0], d[1], d[2], d[3], tag);
        __syncwarp();
        if (lane == 0 && i >= 32 && i < 96) red_cnt(&g_sync[4 * 32 + 2]);
        TS(42);
        {
            const float4 v = get4(&g_M[((lane >> 2) & 1) * 3 * 512 + i * 4 + (lane & 3)], lane < 8, tag);
            if (lane < 8) stsf4(MISC + 96 + lane * 16, v);
        }
        __syncwarp();
        if (lane == 0) {
            if (i < NFFN) {
                wait_cnt(&g_sync[4 * 32 + 2], (ep + 1u) * 64u);
                mbar_wait(BAR(B_KV0FREE));
                asm volatile("fence.proxy.async.global;" ::: "memory");
                mbar_expect_tx(BAR(B_MODV), 16384);
                asm volatile("cp.async.bulk.shared::cluster.global.mbarrier::complete_tx::bytes [%0], [%1], %2, [%3];"
                             ::"r"(sb + OFF_SBCB), "l"(&g_M[512]), "r"(16384), "r"(BAR(B_MODV)) : "memory");
            } else {
                mbar_arrive(BAR(B_MODV));
            }
            TS(45);
        }
    } else {
        const uint32_t ACT = sb + OFF_ACT, ACTB = sb + OFF_ACT + 1152, RED = sb + OFF_RED;
        const int g = lane >> 2, q = lane & 3;
        const int vrr = (lane & 15) >> 1, vb0 = (lane & 1) * 2;
        uint32_t cw[4];
        uint4 xv[2];
        uint32_t xh[4];
        {
            const uint4* xp = reinterpret_cast<const uint4*>(p.x + (warp & 3) * 512 + lane * 16);
            xv[0] = ldnc128_if(xp, warp < 4);
            xv[1] = ldnc128_if(xp + 1, warp < 4);
            const __nv_bfloat16* xq = p.x + vb0 * 512 + jj * 128 + warp * 16 + vrr;
            xh[0] = ldnc16(xq); xh[1] = ldnc16(xq + 512); xh[2] = ldnc16(xq + 8); xh[3] = ldnc16(xq + 520);
        }
#pragma unroll
        for (int b = 0; b < 4; b++) cw[b] = ldnc32(p.c + b * 512 + 2 * t);
        if (lane == 0) {
#pragma unroll
            for (int k = 0; k < 5; k++) {
                int idx = 4 + warp * 5 + k;
                if (idx >= B_YFREE) idx = (idx == 39) ? B_ZFREE : (idx == 40 ? B_P3 : (idx == 41 ? B_CLR2 : B_MODV));
                mbar_init(BAR(0) + idx * 8, 1);
            }
            asm volatile("fence.mbarrier_init.release.cluster;" ::: "memory");
        }
        __syncwarp();
        asm volatile("bar.arrive 5, 320;" ::: "memory");
        asm volatile("bar.arrive 6, 288;" ::: "memory");
        asm volatile("bar.sync 4, 320;" ::: "memory");

#pragma unroll
        for (int b = 0; b < 4; b++) {
            const float c0 = bf_lo(cw[b]), c1 = bf_hi(cw[b]);
            sts32(sb + OFF_S + b * 1040 + t * 4, pack_bf16(__fdividef(c0, 1.f + __expf(-c0)), __fdividef(c1, 1.f + __expf(-c1))));
        }
        if (warp < 4) {
            const uint32_t u[8] = {xv[0].x, xv[0].y, xv[0].z, xv[0].w, xv[1].x, xv[1].y, xv[1].z, xv[1].w};
            float s = 0.f, ss = 0.f;
#pragma unroll
            for (int k = 0; k < 8; k++) s += bf_lo(u[k]) + bf_hi(u[k]);
#pragma unroll
            for (int o = 16; o; o >>= 1) s += __shfl_xor_sync(~0u, s, o);
            const float mean = s * (1.f / 512.f);
#pragma unroll
            for (int k = 0; k < 8; k++) { const float d0 = bf_lo(u[k]) - mean, d1 = bf_hi(u[k]) - mean; ss += d0 * d0 + d1 * d1; }
#pragma unroll
            for (int o = 16; o; o >>= 1) ss += __shfl_xor_sync(~0u, ss, o);
            if (lane == 0) { stsf(MISC + warp * 8, mean); stsf(MISC + warp * 8 + 4, rsqrtf(ss * (1.f / 512.f) + 1e-5f)); }
        }
        bar_main();
        mbar_wait(BAR(B_EP));
        const unsigned int ep = lds32(MISC + 224);
        const uint32_t tag = 1u + 2u * (ep & 1u);
        const uint32_t par = (ep & 1u) ^ 1u;
        if (warp < 2) {
            mbar_wait(BAR(B_WA));
            TS0(26);
            float d[4] = {0.f, 0.f, 0.f, 0.f};
            gemv_512x16(d, sb + OFF_Z + warp * 4096 - jj * 4096, sb + OFF_S, jj * 128, 4, lane);
            if (q < 2) put4(&g_H[i * 32 + warp * 16 + g * 2 + q], d[0], d[1], d[2], d[3], tag);
        }
        TS0(1);
        mbar_wait_n(BAR(B_WQ), 4);
        uint32_t afr[8][4];
        gemv_y_load(afr);
        TS0(3);
        {
            const float4 a = get4sum4(&g_H[(4 * (8 * jj + warp)) * 32 + lane], 32, tag);
            const float cx = __shfl_down_sync(~0u, a.x, 16), cy = __shfl_down_sync(~0u, a.y, 16);
            const float cz = __shfl_down_sync(~0u, a.z, 16), cwv = __shfl_down_sync(~0u, a.w, 16);
            if (lane < 16) {
                const float2 s0 = ldsf2(MISC + vb0 * 8), s1 = ldsf2(MISC + vb0 * 8 + 8);
                sts_frag(ACT, 272, warp * 16 + vrr, vb0,
                         (__uint_as_float(xh[0] << 16) - s0.x) * s0.y * (1.f + cx) + a.x,
                         (__uint_as_float(xh[1] << 16) - s1.x) * s1.y * (1.f + cy) + a.y,
                         (__uint_as_float(xh[2] << 16) - s0.x) * s0.y * (1.f + cz) + a.z,
                         (__uint_as_float(xh[3] << 16) - s1.x) * s1.y * (1.f + cwv) + a.w);
            }
        }
        bar_main();
        TS0(2);
        gemv_y_put(afr, &g_Q[i * 128], ACT, tag);
        __syncwarp();
        if (lane == 0) mbar_arrive(BAR(B_YFREE));
        mbar_wait_n(BAR(B_WUK), 4);
        TS0(5);
        if (warp < 4) {
            const float4 a = get4sum4(&g_Q[hh * 4 * 128 + t], 128, tag);
            sts_frag(ACTB, 272, (t >> 4) * 16 + vrr, vb0, a.x, a.y, a.z, a.w);
        }
        bar_main();
        TS0(4);
        {
            float d[4] = {0.f, 0.f, 0.f, 0.f};
            const int blk = lane >> 3, r8 = lane & 7;
            const uint32_t arow = sb + OFF_X + (warp * 16 + (blk & 1) * 8 + r8) * 128;
            const uint32_t brow = ACTB + (r8 & 3) * 272 + blk * 16;
            uint32_t a[8][4], b[4][4];
#pragma unroll
            for (int k = 0; k < 8; k++) ldsm4(a[k], arow + (k >> 2) * 16384 + ((((k & 3) * 2 + (blk >> 1)) ^ r8) << 4));
#pragma unroll
            for (int k = 0; k < 4; k++) ldsm4(b[k], brow + k * 64);
            float e[4] = {0.f, 0.f, 0.f, 0.f};
#pragma unroll
            for (int k = 0; k < 4; k++) {
                mma16816(d, a[2 * k], b[k][0], b[k][1]);
                mma16816(e, a[2 * k + 1], b[k][2], b[k][3]);
            }
            d[0] += e[0]; d[1] += e[1]; d[2] += e[2]; d[3] += e[3];
            const float sc = 0.08838834764831845f * 1.4426950408889634f;
            if (q < 2) sts_frag(RED, 256, warp * 16 + g, 2 * q, d[0] * sc, d[1] * sc, d[2] * sc, d[3] * sc);
            fence_async_smem();
            bar_main();
            if (t == 0) {
#pragma unroll 1
                for (int b = 0; b < 4; b++) bulk_s2g(&g_qabs[(b * 32 + hh) * 512 + jj * 128], RED + b * 256, 256);
                asm volatile("cp.async.bulk.commit_group;" ::: "memory");
                asm volatile("cp.async.bulk.wait_group 0;" ::: "memory");
#pragma unroll
                for (int r = 0; r < 4; r++) red_cnt(&g_sync[(4 + r) * 32 + 1]);
                mbar_arrive(BAR(B_P3));
            }
            TS0(6);
        }
        const int wg = warp >> 2, wq = warp & 3;
        {
            const uint32_t MX = RED;
            const uint32_t LRED = RED + 512;
            const uint32_t OST = ACTB + 128, PST = ACTB;
            const uint32_t ALPHA = RED + 1536, MRUN = RED + 1664;
            const uint32_t dsc0 = desc_lo(sb);
            float o[4][16];
            float lsum[8];
#pragma unroll
            for (int k = 0; k < 8; k++) lsum[k] = 0.f;
            if (t < 32) stsf(MRUN + t * 4, -INFINITY);
            mbar_wait(BAR(B_QABS));
            TS0(7);
            float s[16];
            auto qk = [&](int c0, int c1) {
                uint32_t da = (dsc0 + (OFF_KV >> 4)) + wg * (65536 >> 4) + c0 * (8192 >> 4), db = (dsc0 + (OFF_X >> 4)) + c0 * (4096 >> 4);
#pragma unroll 1
                for (int cb = c0; cb < c1; cb++) {
                    mbar_wait(BAR(B_KV) + (wg * 8 + cb) * 8);
                    wg_fence();
#pragma unroll
                    for (int k = 0; k < 4; k++) wgmma_n32<0>(s, da + k * 2, db + k * 2, (cb | k) != 0);
                    wg_commit();
                    da += 8192 >> 4;
                    db += 4096 >> 4;
                }
            };
            if (wg == 1) qk(0, QK_EARLY);
#pragma unroll 1
            for (int tile = 0; tile < 2; tile++) {
                if (wg == tile) {
                    qk(tile == 0 ? 0 : QK_EARLY, 8);
                    wg_wait0();
                    reg_fence(s);
                    if (tile == 1) {
                        __syncwarp();
                        if (lane == 0) {
                            mbar_arrive(BAR(B_XFREE));
                            mbar_arrive(BAR(B_KV0FREE));
                            asm volatile("mbarrier.arrive.relaxed.cluster.shared::cluster.b64 _, [%0];" ::"r"(mapa(BAR(B_PEER0), rank ^ 1)) : "memory");
                        }
                    }
                    if (wq == 0) TS(8 + tile * 2);
                    float m[8];
#pragma unroll
                    for (int jb = 0; jb < 4; jb++) {
                        m[2 * jb] = fmaxf(s[4 * jb], s[4 * jb + 2]);
                        m[2 * jb + 1] = fmaxf(s[4 * jb + 1], s[4 * jb + 3]);
                    }
                    {
                        const bool u4 = lane & 16, u3 = lane & 8, u2 = lane & 4;
                        float h4[4], h2[2];
#pragma unroll
                        for (int k = 0; k < 4; k++) h4[k] = fmaxf(u4 ? m[k + 4] : m[k], __shfl_xor_sync(~0u, u4 ? m[k] : m[k + 4], 16));
#pragma unroll
                        for (int k = 0; k < 2; k++) h2[k] = fmaxf(u3 ? h4[k + 2] : h4[k], __shfl_xor_sync(~0u, u3 ? h4[k] : h4[k + 2], 8));
                        const float h1 = fmaxf(u2 ? h2[1] : h2[0], __shfl_xor_sync(~0u, u2 ? h2[0] : h2[1], 4));
                        stsf(MX + (wq * 32 + 8 * (g >> 1) + 2 * q + (g & 1)) * 4, h1);
                    }
                    if (tile == 0) asm volatile("bar.sync 2, 128;" ::: "memory"); else asm volatile("bar.sync 3, 128;" ::: "memory");
                    const float mold = ldsf(MRUN + tile * 128 + lane * 4);
                    const float mnew = fmaxf(fmaxf(fmaxf(ldsf(MX + lane * 4), ldsf(MX + 128 + lane * 4)), fmaxf(ldsf(MX + 256 + lane * 4), ldsf(MX + 384 + lane * 4))), mold);
                    uint32_t lo[4], hi[4];
#pragma unroll
                    for (int jb = 0; jb < 4; jb++) {
                        const float m0 = __shfl_sync(~0u, mnew, 8 * jb + 2 * q), m1 = __shfl_sync(~0u, mnew, 8 * jb + 2 * q + 1);
                        lo[jb] = pack_bf16(ex2(s[4 * jb] - m0), ex2(s[4 * jb + 1] - m1));
                        hi[jb] = pack_bf16(ex2(s[4 * jb + 2] - m0), ex2(s[4 * jb + 3] - m1));
                        lsum[2 * jb] = bf_lo(lo[jb]) + bf_lo(hi[jb]);
                        lsum[2 * jb + 1] = bf_hi(lo[jb]) + bf_hi(hi[jb]);
                    }
                    const uint32_t prow = sb + OFF_P + tile * 4096 + ((lane + 16 * rank) & 31) * 128;
                    stsm4t(prow + (((2 * wq) ^ (lane & 7)) << 4), lo[0], lo[1], lo[2], lo[3]);
                    stsm4t(prow + (((2 * wq + 1) ^ (lane & 7)) << 4), hi[0], hi[1], hi[2], hi[3]);
                    fence_async_smem();
                    if (wq == 0) { stsf(ALPHA + lane * 4, ex2(mold - mnew)); stsf(MRUN + (tile + 1) * 128 + lane * 4, mnew); }
                }
                bar_main();
                TS0(27 + tile);
                if (tile == 1) {
                    wg_wait0();
#pragma unroll
                    for (int mt = 0; mt < 4; mt++) reg_fence(o[mt]);
#pragma unroll
                    for (int jb = 0; jb < 4; jb++) {
                        const float2 a = ldsf2(ALPHA + ((8 * jb + 2 * q + 16 * rank) & 31) * 4);
#pragma unroll
                        for (int mt = 0; mt < 4; mt++) { o[mt][4 * jb] *= a.x; o[mt][4 * jb + 1] *= a.y; o[mt][4 * jb + 2] *= a.x; o[mt][4 * jb + 3] *= a.y; }
                    }
                }
                {
                    const uint32_t da = (dsc0 + (OFF_KV >> 4)) + tile * (65536 >> 4) + wg * (32768 >> 4), db = (dsc0 + (OFF_P >> 4)) + tile * (4096 >> 4);
                    wg_fence();
#pragma unroll
                    for (int mt = 0; mt < 4; mt++) {
#pragma unroll
                        for (int k = 0; k < 4; k++)
                            wgmma_n32<1>(o[mt], da + mt * (8192 >> 4) + k * (2048 >> 4), db + k * 2, tile | k);
                        wg_commit();
                    }
                }
                if (tile == 1) mbar_wait(BAR(B_PEER0));
                if (wg == tile) {
                    {
                        const bool u4 = lane & 16, u3 = lane & 8, u2 = lane & 4;
                        float h4[4], h2[2];
#pragma unroll
                        for (int k = 0; k < 4; k++) h4[k] = (u4 ? lsum[k + 4] : lsum[k]) + __shfl_xor_sync(~0u, u4 ? lsum[k] : lsum[k + 4], 16);
#pragma unroll
                        for (int k = 0; k < 2; k++) h2[k] = (u3 ? h4[k + 2] : h4[k]) + __shfl_xor_sync(~0u, u3 ? h4[k] : h4[k + 2], 8);
                        const float h1 = (u2 ? h2[1] : h2[0]) + __shfl_xor_sync(~0u, u2 ? h2[0] : h2[1], 4);
                        stsf(LRED + (warp * 32 + 8 * (g >> 1) + 2 * q + (g & 1)) * 4, h1);
                    }
                    if (tile == 1) {
                        asm volatile("bar.sync 3, 128;" ::: "memory");
                        if (wq == 0) {
                            float l0 = 0.f, l1 = 0.f;
#pragma unroll
                            for (int w = 0; w < 4; w++) { l0 += ldsf(LRED + (w * 32 + lane) * 4); l1 += ldsf(LRED + ((w + 4) * 32 + lane) * 4); }
                            const float l = l0 * ldsf(ALPHA + lane * 4) + l1;
                            const float mf = ldsf(MRUN + 256 + lane * 4);
                            if ((lane >> 4) == (int)rank) {
                                asm volatile("st.shared.v2.f32 [%0], {%1,%2};" ::"r"(OST + (lane & 15) * 8), "f"(mf), "f"(l) : "memory");
                            } else {
                                st_async2(mapa(PST + (lane & 15) * 8, rank ^ 1), mf, l, mapa(BAR(B_XST), rank ^ 1));
                            }
                            __syncwarp();
                            if (lane == 0) mbar_arrive(BAR(B_XST));
                        }
                    }
                }
                if (tile == 0 && wg == 0) {
                    wg_wait0();
                    __syncwarp();
                    if (lane == 0) {
                        mbar_arrive(BAR(B_KV0FREE));
                        asm volatile("mbarrier.arrive.relaxed.cluster.shared::cluster.b64 _, [%0];" ::"r"(mapa(BAR(B_PEER0), rank ^ 1)) : "memory");
                    }
                    TS0(9);
                }
            }
            {
                const uint32_t rx = mapa(sb + OFF_XCH + t * 16, rank ^ 1), rb = mapa(BAR(B_XCH), rank ^ 1);
                asm volatile("wgmma.wait_group.sync.aligned 3;" ::: "memory");
                reg_fence(o[0]);
                st_async4(rx, pack_bf16(o[0][8], o[0][9]), pack_bf16(o[0][10], o[0][11]), pack_bf16(o[0][12], o[0][13]), pack_bf16(o[0][14], o[0][15]), rb);
                asm volatile("wgmma.wait_group.sync.aligned 2;" ::: "memory");
                reg_fence(o[1]);
                st_async4(rx + 4096, pack_bf16(o[1][8], o[1][9]), pack_bf16(o[1][10], o[1][11]), pack_bf16(o[1][12], o[1][13]), pack_bf16(o[1][14], o[1][15]), rb + 8);
                asm volatile("wgmma.wait_group.sync.aligned 1;" ::: "memory");
                reg_fence(o[2]);
                st_async4(rx + 8192, pack_bf16(o[2][8], o[2][9]), pack_bf16(o[2][10], o[2][11]), pack_bf16(o[2][12], o[2][13]), pack_bf16(o[2][14], o[2][15]), rb + 16);
                wg_wait0();
                reg_fence(o[3]);
                st_async4(rx + 12288, pack_bf16(o[3][8], o[3][9]), pack_bf16(o[3][10], o[3][11]), pack_bf16(o[3][12], o[3][13]), pack_bf16(o[3][14], o[3][15]), rb + 24);
            }
            TS0(11);
            mbar_wait(BAR(B_XST));
            float ca[4], cb[4];
#pragma unroll
            for (int k = 0; k < 4; k++) {
                const int n = 8 * (k >> 1) + 2 * q + (k & 1);
                const float2 so = ldsf2(OST + n * 8), sp = ldsf2(PST + n * 8);
                const float mx = fmaxf(so.x, sp.x);
                ca[k] = ex2(so.x - mx);
                cb[k] = ex2(sp.x - mx);
            }
#pragma unroll
            for (int mt = 0; mt < 4; mt++) {
                o[mt][0] *= ca[0]; o[mt][1] *= ca[1]; o[mt][2] *= ca[0]; o[mt][3] *= ca[1];
                o[mt][4] *= ca[2]; o[mt][5] *= ca[3]; o[mt][6] *= ca[2]; o[mt][7] *= ca[3];
            }
            if (warp == 0) {
                const float2 so = ldsf2(OST + (lane & 15) * 8), sp = ldsf2(PST + (lane & 15) * 8);
                const float mx = fmaxf(so.x, sp.x);
                const float l = so.y * ex2(so.x - mx) + sp.y * ex2(sp.x - mx);
                const float ln = __shfl_down_sync(~0u, l, 1), mn = __shfl_down_sync(~0u, mx, 1);
                if (lane < 16 && (lane & 1) == 0) put4(&g_stat[((rank * 4 + (lane >> 2)) * 64 + (i >> 1)) * 2 + ((lane >> 1) & 1)], mx, l, mn, ln, tag);
            }
            const uint32_t keep = (g == 0) ? 0xFFFEFFFEu : 0xFFFFFFFFu;
            const uint32_t tg = (g == 0) ? ((ep & 1u) ? 0u : 0x00010001u) : 0u;
            const int hl = lane & 15, mi2 = lane >> 4;
#pragma unroll
            for (int mt = 0; mt < 4; mt++) {
                mbar_wait(BAR(B_XCH + mt));
                if (mt == 3) TS0(46);
                const uint4 r = lds128(sb + OFF_XCH + mt * 4096 + t * 16);
                const uint32_t lo0 = (pack_bf16(o[mt][0] + cb[0] * bf_lo(r.x), o[mt][1] + cb[1] * bf_hi(r.x)) & keep) | tg;
                const uint32_t hi0 = (pack_bf16(o[mt][2] + cb[0] * bf_lo(r.y), o[mt][3] + cb[1] * bf_hi(r.y)) & keep) | tg;
                const uint32_t lo1 = (pack_bf16(o[mt][4] + cb[2] * bf_lo(r.z), o[mt][5] + cb[3] * bf_hi(r.z)) & keep) | tg;
                const uint32_t hi1 = (pack_bf16(o[mt][6] + cb[2] * bf_lo(r.w), o[mt][7] + cb[3] * bf_hi(r.w)) & keep) | tg;
                const uint32_t row = sb + OFF_STG + (wg * 2 + (mt >> 1)) * 4096 + hl * 256;
                const int ch = (mt & 1) * 8 + wq * 2 + mi2;
                stsm4t(row + ((ch ^ (hl & 7)) << 4), lo0, lo1, hi0, hi1);
            }
            fence_async_smem();
            if (wg == 0) asm volatile("bar.sync 2, 128;" ::: "memory"); else asm volatile("bar.sync 3, 128;" ::: "memory");
            if (warp == 4) TS(47);
            if (wq == 0 && lane == 0) {
                bulk_s2g(&g_part[i * 1024 + wg * 512], sb + OFF_STG + wg * 8192, 8192);
                asm volatile("cp.async.bulk.commit_group;" ::: "memory");
                asm volatile("cp.async.bulk.wait_group 0;" ::: "memory");
                if (atomicAdd(reinterpret_cast<unsigned int*>(smem + OFF_MISC + 236), 1u) == 1u) red_cnt(&g_sync[bb * 32 + 1]);
            }
            TS0(12);
        }
        mbar_wait(BAR(B_CLR2));
        const uint32_t SCR = sb + OFF_SCR;
        {
            const int b = warp >> 1;
            const uint32_t ptag = par;
            const int pi = lane >> 3, v = (warp & 1) * 8 + (lane & 7);
            const uint4* sp = &g_stat[((hh >> 2) * 64 + b * 16 + (lane & 15)) * 2 + ((hh >> 1) & 1)];
            const uint4* src = &g_part[(2 * (b * 16 + pi) + (hh >> 4)) * 1024 + (jj * 16 + (hh & 15)) * 16 + v];
            float acc[8];
            int it = 0;
            bool ok;
            mbar_wait_n(BAR(B_WUV), 4);
            gemv_y_load(afr);
            float wi;
            {
                const unsigned int t_stat = lds32(MISC + 232) - STAT_LEAD;
#pragma unroll 1
                while ((int)(gtimer_lo() - t_stat) < 0 && ++it < SPIN_LIMIT) {}
                const float4 su = get4(sp, true, tag);
                const float mi = (hh & 1) ? su.z : su.x, li = (hh & 1) ? su.w : su.y;
                float mx = mi;
#pragma unroll
                for (int of = 8; of; of >>= 1) mx = fmaxf(mx, __shfl_xor_sync(~0u, mx, of));
                wi = ex2(mi - mx);
                float L = wi * li;
#pragma unroll
                for (int of = 8; of; of >>= 1) L += __shfl_xor_sync(~0u, L, of);
                wi = __fdividef(wi, L);
            }
            float w4[4];
#pragma unroll
            for (int k = 0; k < 4; k++) w4[k] = __shfl_sync(~0u, wi, 4 * k + pi);
            mbar_wait(BAR(B_G4));
            it = 0;
#pragma unroll 1
            do {
                uint4 r[4];
#pragma unroll
                for (int k = 0; k < 4; k++) r[k] = ld128(src + (size_t)k * 8 * 1024);
                ok = true;
#pragma unroll
                for (int k = 0; k < 8; k++) acc[k] = 0.f;
#pragma unroll
                for (int k = 0; k < 4; k++) {
                    const float w = w4[k];
                    ok = ok & ((r[k].x & 1u) == ptag);
                    acc[0] += w * bf_lo(r[k].x); acc[1] += w * bf_hi(r[k].x);
                    acc[2] += w * bf_lo(r[k].y); acc[3] += w * bf_hi(r[k].y);
                    acc[4] += w * bf_lo(r[k].z); acc[5] += w * bf_hi(r[k].z);
                    acc[6] += w * bf_lo(r[k].w); acc[7] += w * bf_hi(r[k].w);
                }
            } while (!__all_sync(~0u, ok) && ++it < SPIN_LIMIT);
            {
                const bool u4 = lane & 16, u3 = lane & 8;
                float h4[4], h2[2];
#pragma unroll
                for (int k = 0; k < 4; k++) h4[k] = (u4 ? acc[k + 4] : acc[k]) + __shfl_xor_sync(~0u, u4 ? acc[k] : acc[k + 4], 16);
#pragma unroll
                for (int k = 0; k < 2; k++) h2[k] = (u3 ? h4[k + 2] : h4[k]) + __shfl_xor_sync(~0u, u3 ? h4[k] : h4[k + 2], 8);
                const int ch = v ^ (hh & 7);
                sts32(ACT + b * 272 + (ch * 8 + (u4 ? 4 : 0) + (u3 ? 2 : 0)) * 2, pack_bf16(h2[0], h2[1]));
            }
            bar_main();
            TS0(14);
        }
        gemv_y_put(afr, &g_C[i * 128], ACT, tag);
        TS0(17);
        mbar_wait_n(BAR(B_WO), 4);
        {
            const int blk = lane >> 3, r8 = lane & 7;
            const uint32_t wb = sb + OFF_X + warp * 4096 + ((blk >> 1) * 8 + r8) * 128;
#pragma unroll
            for (int mt = 0; mt < 4; mt++) {
                const uint32_t co = ((2 * mt + (blk & 1)) ^ r8) << 4;
                ldsm4t(afr[2 * mt], wb + co);
                ldsm4t(afr[2 * mt + 1], wb + 16 * 128 + co);
            }
        }
        if (warp == 0) {
            const float4 a = get4sum4(&g_C[hh * 4 * 128 + jj * 32 + lane], 128, tag);
            sts_frag(ACTB, 80, (t >> 4) * 16 + vrr, vb0, a.x, a.y, a.z, a.w);
        }
        bar_main();
        TS0(16);
        {
            uint32_t b[4];
            ldsm4(b, ACTB + (lane & 3) * 80 + (lane >> 3) * 16);
            uint32_t px[4], py[4];
#pragma unroll
            for (int mt = 0; mt < 4; mt++) {
                float d[4] = {0.f, 0.f, 0.f, 0.f};
                mma16816(d, afr[2 * mt], b[0], b[1]);
                mma16816(d, afr[2 * mt + 1], b[2], b[3]);
                px[mt] = (pack_bf16(d[0], d[1]) & ~1u) | par;
                py[mt] = pack_bf16(d[2], d[3]);
            }
            if (q < 2) {
                uint2* dst = &g_O[i * 512 + warp * 64 + g * 2 + q];
#pragma unroll
                for (int mt = 0; mt < 4; mt++) st64(dst + mt * 16, px[mt], py[mt]);
            }
            TS0(18);
        }
        const int V = i * 4 + (t & 3);
        const int vm = (V >> 4) * 16 + ((V & 15) >> 1), vb = (V & 1) * 2;
        float4 x1 = make_float4(0.f, 0.f, 0.f, 0.f);
        {
            mbar_wait(BAR(B_MODV));
            const float4 r = reduce16(g_O, 128, par, G6ADELAY);
            if (t < 4) {
                const float4 x0 = ldsf4(MISC + 32 + t * 16), ga = ldsf4(MISC + 96 + t * 16);
                x1 = make_float4(x0.x + ga.x * r.x, x0.y + ga.y * r.y, x0.z + ga.z * r.z, x0.w + ga.w * r.w);
                put2(&g_X1[i * 8 + t], x1.x, x1.y, x1.z, x1.w, par);
            }
            TS0(19);
        }
        if (i < NFFN) {
            float4 mv[4];
#pragma unroll
            for (int k = 0; k < 4; k++) {
                uint4 u = lds128(sb + OFF_SBCB + (t + 256 * k) * 16);
                int it = 0;
                while ((u.x & 3u) != tag && ++it < SPIN_LIMIT) u = ld128(&g_M[512 + t + 256 * k]);
                mv[k] = as_f4(u);
            }
            mbar_wait_n(BAR(B_W1), 4);
            {
                const int blk = lane >> 3, r8 = lane & 7;
                const uint32_t w1r = sb + OFF_Z + (warp * 64 + (blk >> 1) * 8 + r8) * 32 + (((blk & 1) ^ ((r8 >> 2) & 1)) << 4);
                const uint32_t w2r = sb + OFF_W2 + warp * 2048 + ((blk >> 1) * 8 + r8) * 128;
#pragma unroll
                for (int k = 0; k < 4; k++) {
                    ldsm4t(afr[k], w1r + k * 512);
                    ldsm4t(afr[4 + k], w2r + (((2 * k + (blk & 1)) ^ r8) << 4));
                }
            }
            TS0(21);
            uint2 ua, ub;
            {
                int it = 0;
#pragma unroll 1
                do { ua = ld64(&g_X1[(t >> 2) * 8 + (t & 3)]); ub = ld64(&g_X1[(t >> 2) * 8 + (t & 3) + 512]); } while (!__all_sync(~0u, (((ua.x ^ par) | (ub.x ^ par)) & 1u) == 0) && ++it < SPIN_LIMIT);
            }
            const float4 a = as_f4(ua), b = as_f4(ub);
            float s0 = (a.x + a.z) + (b.x + b.z), s1 = (a.y + a.w) + (b.y + b.w);
            float q0 = (a.x * a.x + a.z * a.z) + (b.x * b.x + b.z * b.z), q1 = (a.y * a.y + a.w * a.w) + (b.y * b.y + b.w * b.w);
#pragma unroll
            for (int of = 2; of <= 16; of <<= 1) {
                s0 += __shfl_xor_sync(~0u, s0, of); s1 += __shfl_xor_sync(~0u, s1, of);
                q0 += __shfl_xor_sync(~0u, q0, of); q1 += __shfl_xor_sync(~0u, q1, of);
            }
            const uint32_t ST = SCR + 1024, ACT2 = SCR + 4096;
            if (lane < 2) stsf4(ST + (warp * 2 + lane) * 16, make_float4(s0, q0, s1, q1));
            bar_main();
            TS0(20);
            float4 tot = make_float4(0.f, 0.f, 0.f, 0.f);
#pragma unroll
            for (int w = 0; w < 8; w++) add4(tot, ldsf4(ST + (w * 2 + (t & 1)) * 16));
            const float mean0 = tot.x * (1.f / 512.f), mean1 = tot.z * (1.f / 512.f);
            const float r0 = rsqrtf(fmaxf(tot.y * (1.f / 512.f) - mean0 * mean0, 0.f) + 1e-5f);
            const float r1 = rsqrtf(fmaxf(tot.w * (1.f / 512.f) - mean1 * mean1, 0.f) + 1e-5f);
            const int m0 = (t >> 4) * 16 + vrr;
            sts_frag(ACT2, 1040, m0, vb0, (a.x - mean0) * r0 * (1.f + mv[2].x) + mv[0].x, (a.y - mean1) * r1 * (1.f + mv[2].y) + mv[0].y,
                     (a.z - mean0) * r0 * (1.f + mv[2].z) + mv[0].z, (a.w - mean1) * r1 * (1.f + mv[2].w) + mv[0].w);
            sts_frag(ACT2, 1040, m0 + 256, vb0, (b.x - mean0) * r0 * (1.f + mv[3].x) + mv[1].x, (b.y - mean1) * r1 * (1.f + mv[3].y) + mv[1].y,
                     (b.z - mean0) * r0 * (1.f + mv[3].z) + mv[1].z, (b.w - mean1) * r1 * (1.f + mv[3].w) + mv[1].w);
            bar_main();
            float d[4] = {0.f, 0.f, 0.f, 0.f};
            {
                const uint32_t brow = ACT2 + (lane & 3) * 1040 + (warp * 64 + (lane >> 3) * 8) * 2;
                uint32_t b0[4], b1[4];
                ldsm4(b0, brow);
                ldsm4(b1, brow + 64);
                float e[4] = {0.f, 0.f, 0.f, 0.f};
                mma16816(d, afr[0], b0[0], b0[1]);
                mma16816(e, afr[1], b0[2], b0[3]);
                mma16816(d, afr[2], b1[0], b1[1]);
                mma16816(e, afr[3], b1[2], b1[3]);
                d[0] += e[0]; d[1] += e[1]; d[2] += e[2]; d[3] += e[3];
            }
            const uint32_t HR = SCR + 2048;
            if (q < 2) {
                const uint32_t a0 = HR + (warp * 64 + (2 * q) * 16 + (g >> 1) * 4 + (g & 1)) * 4;
                stsf(a0, d[0]); stsf(a0 + 64, d[1]); stsf(a0 + 8, d[2]); stsf(a0 + 72, d[3]);
            }
            bar_main();
            float4 hs = ldsf4(HR + ((g & 3) * 16 + q * 4) * 4);
#pragma unroll
            for (int w = 1; w < 8; w++) add4(hs, ldsf4(HR + (w * 64 + (g & 3) * 16 + q * 4) * 4));
            const uint32_t b0r = pack_bf16(fmaxf(hs.x, 0.f), fmaxf(hs.y, 0.f)), b1r = pack_bf16(fmaxf(hs.z, 0.f), fmaxf(hs.w, 0.f));
            TS0(22);
            uint32_t px[4], py[4];
#pragma unroll
            for (int mt = 0; mt < 4; mt++) {
                float e[4] = {0.f, 0.f, 0.f, 0.f};
                mma16816(e, afr[4 + mt], b0r, b1r);
                px[mt] = (pack_bf16(e[0], e[1]) & ~1u) | par;
                py[mt] = pack_bf16(e[2], e[3]);
            }
            if (q < 2) {
                uint2* dst = &g_F[i * 512 + warp * 64 + g * 2 + q];
#pragma unroll
                for (int mt = 0; mt < 4; mt++) st64(dst + mt * 16, px[mt], py[mt]);
            }
            TS0(23);
        }
        {
            const float4 r = reduce16(g_F, NFFN, par, i < NFFN ? HOPDELAY : FFNDELAY);
            if (t < 4) {
                const float4 gb = ldsf4(MISC + 96 + 64 + t * 16);
                p.out[vb * 512 + vm] = __float2bfloat16_rn(x1.x + gb.x * r.x);
                p.out[(vb + 1) * 512 + vm] = __float2bfloat16_rn(x1.y + gb.y * r.y);
                p.out[vb * 512 + vm + 8] = __float2bfloat16_rn(x1.z + gb.z * r.z);
                p.out[(vb + 1) * 512 + vm + 8] = __float2bfloat16_rn(x1.w + gb.w * r.w);
            }
            if (i == 0 && t < NSYNC) g_sync[t * 32] = ep + 1u;
            TS0(24);
        }
    }
}

typedef CUresult (*EncodeFn)(CUtensorMap*, CUtensorMapDataType, cuuint32_t, void*, const cuuint64_t*, const cuuint64_t*, const cuuint32_t*,
                             const cuuint32_t*, CUtensorMapInterleave, CUtensorMapSwizzle, CUtensorMapL2promotion, CUtensorMapFloatOOBfill);

void make_map(EncodeFn enc, CUtensorMap* m, const void* base, int rank, const cuuint64_t* dims, const cuuint64_t* strides, const cuuint32_t* box,
              CUtensorMapSwizzle sw) {
    cuuint32_t es[3] = {1, 1, 1};
    CUresult r = enc(m, CU_TENSOR_MAP_DATA_TYPE_BFLOAT16, rank, const_cast<void*>(base), dims, strides, box, es, CU_TENSOR_MAP_INTERLEAVE_NONE, sw,
                     CU_TENSOR_MAP_L2_PROMOTION_NONE, CU_TENSOR_MAP_FLOAT_OOB_FILL_NONE);
    if (r != CUDA_SUCCESS) fprintf(stderr, "cuTensorMapEncodeTiled failed: %d\n", (int)r);
}
void map2d(EncodeFn enc, CUtensorMap* m, const void* base, uint64_t rows, uint64_t cols, uint32_t boxr, uint32_t boxc, CUtensorMapSwizzle sw) {
    cuuint64_t dims[2] = {cols, rows};
    cuuint64_t strides[1] = {cols * 2};
    cuuint32_t box[2] = {boxc, boxr};
    make_map(enc, m, base, 2, dims, strides, box, sw);
}
void map3d(EncodeFn enc, CUtensorMap* m, const void* base, uint64_t rows, uint32_t boxr, uint32_t boxb) {
    cuuint64_t dims[3] = {64, rows, 8};
    cuuint64_t strides[2] = {1024, 128};
    cuuint32_t box[3] = {64, boxr, boxb};
    make_map(enc, m, base, 3, dims, strides, box, CU_TENSOR_MAP_SWIZZLE_128B);
}

}

extern "C" void kernel_launch(void* const* d_in, const int* in_sizes, int n_in, void* d_out, int out_size) {
    (void)in_sizes; (void)n_in; (void)out_size;
    static EncodeFn enc = nullptr;
    static void* qabs_ptr = nullptr;
    static bool fits = false;
    if (!enc) {
        void* fn = nullptr;
        cudaDriverEntryPointQueryResult st;
        cudaGetDriverEntryPoint("cuTensorMapEncodeTiled", &fn, cudaEnableDefault, &st);
        enc = (EncodeFn)fn;
        cudaFuncSetAttribute(fused_kernel, cudaFuncAttributeMaxDynamicSharedMemorySize, SMEM_BYTES);
        cudaGetSymbolAddress(&qabs_ptr, g_qabs);
        cudaLaunchConfig_t cfg = {};
        cfg.gridDim = dim3(NCTA);
        cfg.blockDim = dim3(NTHREADS);
        cfg.dynamicSmemBytes = SMEM_BYTES;
        cudaLaunchAttribute at[1];
        at[0].id = cudaLaunchAttributeClusterDimension;
        at[0].val.clusterDim.x = 2; at[0].val.clusterDim.y = 1; at[0].val.clusterDim.z = 1;
        cfg.attrs = at;
        cfg.numAttrs = 1;
        int nclusters = 0;
        if (cudaOccupancyMaxActiveClusters(&nclusters, fused_kernel, &cfg) != cudaSuccess) { (void)cudaGetLastError(); nclusters = NCTA / 2; }
        fits = nclusters >= NCTA / 2;
        if (!fits) fprintf(stderr, "fused_kernel: only %d of %d clusters can be resident on this device\n", nclusters, NCTA / 2);
    }
    if (!enc || !fits) return;
    Params p;
    map2d(enc, &p.kv, d_in[1], 16384, 512, 64, 64, CU_TENSOR_MAP_SWIZZLE_128B);
    map2d(enc, &p.wq, d_in[2], 512, 4096, 64, 64, CU_TENSOR_MAP_SWIZZLE_128B);
    map2d(enc, &p.wuk, d_in[3], 512, 4096, 64, 64, CU_TENSOR_MAP_SWIZZLE_128B);
    map2d(enc, &p.wuv, d_in[4], 512, 4096, 64, 64, CU_TENSOR_MAP_SWIZZLE_128B);
    map3d(enc, &p.wo, d_in[5], 4096, 32, 2);
    map2d(enc, &p.w1, d_in[7], 512, 1376, 256, 16, CU_TENSOR_MAP_SWIZZLE_32B);
    map3d(enc, &p.w2, d_in[8], 1376, 16, 4);
    map2d(enc, &p.wmod, d_in[10], 512, 3072, 256, 16, CU_TENSOR_MAP_SWIZZLE_32B);
    map3d(enc, &p.qabs, qabs_ptr, 128, 32, 4);
    map2d(enc, &p.wmoda, d_in[10], 512, 3072, 128, 16, CU_TENSOR_MAP_SWIZZLE_32B);
    p.x = (const __nv_bfloat16*)d_in[0];
    p.c = (const __nv_bfloat16*)d_in[9];
    p.out = (__nv_bfloat16*)d_out;
    fused_kernel<<<NCTA, NTHREADS, SMEM_BYTES, cudaStreamPerThread>>>(p);
}
```
